```python
import torch

def _softmax(x, axis=-1):
    return torch.softmax(x, dim=axis)
def _gelu(x):
    return torch.nn.functional.gelu(x, approximate="tanh")
def _silu(x):
    return torch.nn.functional.silu(x)
def _sigmoid(x):
    return torch.sigmoid(x)
def _layernorm(x, axis=-1, eps=1e-5):
    m = x.mean(dim=axis, keepdim=True)
    v = x.var(dim=axis, keepdim=True, unbiased=False)
    return (x - m) / torch.sqrt(v + eps)
def _scatter_add(tgt, idx, src, axis=0):
    return tgt.clone().index_add_(axis, idx, src)
def _segment_sum(src, seg, n):
    out = torch.zeros((n,) + src.shape[1:], dtype=src.dtype)
    return out.index_add_(0, seg, src)
def _pad(x, pw):
    flat = tuple(v for pair in reversed(pw) for v in pair)
    return torch.nn.functional.pad(x, flat)

kernel_name = 'parallel_sum__sliding_block_cached__glu_gated_reglu__decode'

def setup_inputs():

    _w = (lambda a: (lambda t: t.to(torch.bfloat16) if t.is_floating_point() else t)(torch.as_tensor(a)))
    def _A_setup():
        B, Sq, D = 2, 1, 448
        Hq, Hkv, Sk, Dh = 16, 8, 32768, 256
        assert Hq % Hkv == 0, (Hq, Hkv)
        return {
            "x": _w((lambda *s: torch.randn(*s, dtype=torch.bfloat16) * 0.05)(B, Sq, D)),
            "k_cache": _w((lambda *s: torch.randn(*s, dtype=torch.bfloat16) * 1.6)(B, Hkv, Sk, Dh)),
            "v_cache": _w((lambda *s: torch.randn(*s, dtype=torch.bfloat16) * 0.8)(B, Hkv, Sk, Dh)),
            "wq": _w((lambda *s: torch.randn(*s, dtype=torch.bfloat16) * 1.6)(D, Hq * Dh) * (D ** -0.5)),
            "wo": _w((lambda *s: torch.randn(*s, dtype=torch.bfloat16) * 0.8)(Hq * Dh, D) * ((Hq * Dh) ** -0.5)),
        }
    _A_in = _A_setup()

    def _B_setup():
        B, S, D, F = 2, 1, 448, 1792
        return {
            "x": _w((lambda *s: torch.randn(*s, dtype=torch.bfloat16) * 0.05)(B, S, D)),
            "W_gate": _w((lambda *s: torch.randn(*s, dtype=torch.bfloat16) * 0.4)(D, F) * (2.0 / D) ** 0.5),
            "W_up": _w((lambda *s: torch.randn(*s, dtype=torch.bfloat16) * 0.4)(D, F) * (2.0 / D) ** 0.5),
            "W_down": _w((lambda *s: torch.randn(*s, dtype=torch.bfloat16) * 0.4)(F, D) * (1.0 / F) ** 0.5),
        }
    _B_in = _B_setup()

    return {
        "A_x": _A_in["x"],
        "A_k_cache": _A_in["k_cache"],
        "A_v_cache": _A_in["v_cache"],
        "A_wq": _A_in["wq"],
        "A_wo": _A_in["wo"],
        "B_x": _B_in["x"],
        "B_W_gate": _B_in["W_gate"],
        "B_W_up": _B_in["W_up"],
        "B_W_down": _B_in["W_down"],
    }

def reference(A_x, A_k_cache, A_v_cache, A_wq, A_wo, B_x, B_W_gate, B_W_up, B_W_down):
    def _A_ref(x, k_cache, v_cache, wq, wo):
        B, Sq, D = x.shape
        Hq, Dh = 16, 256
        Hkv, Sk = k_cache.shape[1], k_cache.shape[2]
        W = min(4096, max(256, Sk // 4))
        rep = Hq // Hkv
        q = (lambda x, *d: x.permute(*d))((x @ wq).reshape(B, Sq, Hq, Dh), 0, 2, 1, 3)
        k = (lambda x, n, axis: torch.repeat_interleave(x, n, dim=axis))(k_cache[:, :, Sk - W:, :], rep, axis=1)
        v = (lambda x, n, axis: torch.repeat_interleave(x, n, dim=axis))(v_cache[:, :, Sk - W:, :], rep, axis=1)
        scores = torch.einsum("bhqd,bhkd->bhqk", q, k) * (Dh ** -0.5)
        p = _softmax(scores, axis=-1)
        o = torch.einsum("bhqk,bhkd->bhqd", p, v)
        return (lambda x, *d: x.permute(*d))(o, 0, 2, 1, 3).reshape(B, Sq, Hq * Dh) @ wo

    def _B_ref(x, W_gate, W_up, W_down):
        gate = torch.einsum("bsd,df->bsf", x, W_gate)
        up = torch.einsum("bsd,df->bsf", x, W_up)
        gate = gate * (lambda x, dt: x.to(dt))(gate > 0, gate.dtype)
        h = gate * up
        return torch.einsum("bsf,fd->bsd", h, W_down)

    x = A_x
    xn = _layernorm(x, axis=-1)
    return x + _A_ref(xn, A_k_cache, A_v_cache, A_wq, A_wo) + _B_ref(xn, B_W_gate, B_W_up, B_W_down)
```

```cpp
#include <cuda_runtime.h>
#include <cuda_bf16.h>
#include <stdint.h>

namespace {

constexpr int DM = 448, FF = 1792, SK = 32768, WIN = 4096, DH = 256, QD = 4096;
constexpr int NCTA = 128, NFFN = 112;
constexpr int TILE_KEYS = 64, TILE_BYTES = TILE_KEYS * 512, NT = 512 / TILE_KEYS;
#define STAGES_ 4
constexpr int STAGES = STAGES_;
constexpr int NTHREADS = 320;
constexpr int WO_BYTES = 32 * DM * 2, WD_BYTES = 16 * DM * 2;
constexpr uint32_t SPIN_LIMIT = 1u << 22;

constexpr int SM_RING = 0;
constexpr int SM_WO = SM_RING + STAGES * TILE_BYTES;
constexpr int SM_WD = SM_WO + WO_BYTES;
constexpr int SM_SP = SM_WD + WD_BYTES;
constexpr int SM_PW = SM_SP + 8192;
constexpr int SM_XN = SM_PW + 2048;
constexpr int SM_QS = SM_XN + 3584;
constexpr int SM_RED = SM_QS + 1024;
constexpr int SM_VEC = SM_RED + 4096;
constexpr int SM_ST = SM_VEC + 192;
constexpr int SM_BAR = SM_ST + 192;
constexpr int NBAR_FULL = 2 * NT, BAR_WD = NBAR_FULL, BAR_WO = NBAR_FULL + 1, BAR_EMPTY = NBAR_FULL + 2;
constexpr int NBAR = BAR_EMPTY + 2 * NT - STAGES;
constexpr int SM_TOTAL = SM_BAR + NBAR * 8;
static_assert(NBAR <= 32, "one lane per barrier");

__device__ uint32_t g_q[16 * 256];
__device__ uint4 g_ml[NCTA];
__device__ uint4 g_o[NCTA * 256];
__device__ uint4 g_f[NFFN * 256];
#define STAMP(i)

__device__ __forceinline__ void mbar_init(uint32_t bar, uint32_t cnt) {
    asm volatile("mbarrier.init.shared::cta.b64 [%0], %1;" ::"r"(bar), "r"(cnt) : "memory");
}
__device__ __forceinline__ void mbar_expect(uint32_t bar, uint32_t bytes) {
    asm volatile("mbarrier.arrive.expect_tx.shared::cta.b64 _, [%0], %1;" ::"r"(bar), "r"(bytes) : "memory");
}
__device__ __forceinline__ void mbar_arrive(uint32_t bar) {
    asm volatile("mbarrier.arrive.shared::cta.b64 _, [%0];" ::"r"(bar) : "memory");
}
__device__ __forceinline__ void mbar_wait(uint32_t bar) {
    uint32_t done, n = 0;
    do {
        asm volatile("{\n.reg .pred p;\nmbarrier.try_wait.parity.shared::cta.b64 p, [%1], 0;\nselp.u32 %0, 1, 0, p;\n}"
                     : "=r"(done) : "r"(bar) : "memory");
        if (++n > SPIN_LIMIT) __trap();
    } while (!done);
}
__device__ __forceinline__ void bulk_load(uint32_t dst, const void* src, uint32_t bytes, uint32_t bar, uint64_t pol) {
    mbar_expect(bar, bytes);
    asm volatile("cp.async.bulk.shared::cluster.global.mbarrier::complete_tx::bytes.L2::cache_hint [%0], [%1], %2, [%3], %4;"
                 ::"r"(dst), "l"(src), "r"(bytes), "r"(bar), "l"(pol) : "memory");
}
__device__ __forceinline__ void bar_sync(int id, int n) { asm volatile("bar.sync %0, %1;" ::"r"(id), "r"(n) : "memory"); }
__device__ __forceinline__ void bar_arrive(int id, int n) { asm volatile("bar.arrive %0, %1;" ::"r"(id), "r"(n) : "memory"); }
__device__ __forceinline__ uint4 lds128(uint32_t a) {
    uint4 v;
    asm volatile("ld.shared.v4.u32 {%0,%1,%2,%3}, [%4];" : "=r"(v.x), "=r"(v.y), "=r"(v.z), "=r"(v.w) : "r"(a) : "memory");
    return v;
}
__device__ __forceinline__ uint4 ldg_nc(const void* p) {
    uint4 v;
    asm volatile("ld.global.nc.L1::no_allocate.v4.u32 {%0,%1,%2,%3}, [%4];" : "=r"(v.x), "=r"(v.y), "=r"(v.z), "=r"(v.w) : "l"(p));
    return v;
}
__device__ __forceinline__ uint4 ld_poll(const uint4* p) {
    uint4 v;
    asm volatile("ld.relaxed.gpu.global.v4.u32 {%0,%1,%2,%3}, [%4];" : "=r"(v.x), "=r"(v.y), "=r"(v.z), "=r"(v.w) : "l"(p) : "memory");
    return v;
}
__device__ __forceinline__ void st_pub(uint4* p, uint4 v) {
    asm volatile("st.relaxed.gpu.global.v4.u32 [%0], {%1,%2,%3,%4};" ::"l"(p), "r"(v.x), "r"(v.y), "r"(v.z), "r"(v.w) : "memory");
}
__device__ __forceinline__ void st_pub32(uint32_t* p, uint32_t v) {
    asm volatile("st.relaxed.gpu.global.u32 [%0], %1;" ::"l"(p), "r"(v) : "memory");
}
__device__ __forceinline__ bool valid4(const uint4& v) { return v.x != 0 && v.y != 0 && v.z != 0 && v.w != 0; }
__device__ __forceinline__ uint32_t nz(float f) { uint32_t u = __float_as_uint(f); return u == 0 ? 0x80000000u : u; }
__device__ __forceinline__ void mma16816(float (&c)[4], uint32_t a0, uint32_t a1, uint32_t a2, uint32_t a3, uint32_t b0, uint32_t b1) {
    asm volatile("mma.sync.aligned.m16n8k16.row.col.f32.bf16.bf16.f32 {%0,%1,%2,%3}, {%4,%5,%6,%7}, {%8,%9}, {%0,%1,%2,%3};"
                 : "+f"(c[0]), "+f"(c[1]), "+f"(c[2]), "+f"(c[3]) : "r"(a0), "r"(a1), "r"(a2), "r"(a3), "r"(b0), "r"(b1));
}
__device__ __forceinline__ float bf_lo(uint32_t w) { return __uint_as_float(w << 16); }
__device__ __forceinline__ float bf_hi(uint32_t w) { return __uint_as_float(w & 0xffff0000u); }
__device__ __forceinline__ float rbf(float f) { return __bfloat162float(__float2bfloat16_rn(f)); }
__device__ __forceinline__ uint32_t pack_bf(float lo, float hi) {
    uint32_t r;
    asm("cvt.rn.bf16x2.f32 %0, %1, %2;" : "=r"(r) : "f"(hi), "f"(lo));
    return r;
}
__device__ __forceinline__ float shx(float v, int m) { return __shfl_xor_sync(0xffffffffu, v, m); }

__device__ __forceinline__ void vm_step(float (&acc)[4][4], const uint4& X, const uint4& Y, uint32_t wa, uint32_t wb,
                                        uint32_t sel0, uint32_t sel1) {
    const uint32_t a0 = __byte_perm(wa, 0, sel0), a1 = __byte_perm(wa, 0, sel1);
    const uint32_t a2 = __byte_perm(wb, 0, sel0), a3 = __byte_perm(wb, 0, sel1);
    mma16816(acc[0], a0, a1, a2, a3, X.x, Y.x);
    mma16816(acc[1], a0, a1, a2, a3, X.y, Y.y);
    mma16816(acc[2], a0, a1, a2, a3, X.z, Y.z);
    mma16816(acc[3], a0, a1, a2, a3, X.w, Y.w);
}
__device__ __forceinline__ void vm_reduce(const float (&acc)[4][4], float (&r)[4], int a) {
    const bool hi = a & 2, od = a & 1;
#pragma unroll
    for (int u = 0; u < 4; u++) {
        const float k0 = hi ? acc[u][2] : acc[u][0], k1 = hi ? acc[u][3] : acc[u][1];
        const float s0 = hi ? acc[u][0] : acc[u][2], s1 = hi ? acc[u][1] : acc[u][3];
        const float v0 = k0 + shx(s0, 18), v1 = k1 + shx(s1, 18);
        r[u] = (od ? v1 : v0) + shx(od ? v0 : v1, 9);
    }
}

__device__ __forceinline__ void gemv0(const uint4 (&w)[7], const float2* xn, int r0, int lane, float2* red) {
    float a0[8], a1[8];
#pragma unroll
    for (int e = 0; e < 8; e++) a0[e] = a1[e] = 0.f;
#pragma unroll
    for (int i = 0; i < 7; i++) {
        const float2 xv = xn[r0 + 64 * i];
        const uint32_t ww[4] = {w[i].x, w[i].y, w[i].z, w[i].w};
#pragma unroll
        for (int e = 0; e < 4; e++) {
            const float lo = bf_lo(ww[e]), hi = bf_hi(ww[e]);
            a0[2 * e] = fmaf(xv.x, lo, a0[2 * e]);
            a0[2 * e + 1] = fmaf(xv.x, hi, a0[2 * e + 1]);
            a1[2 * e] = fmaf(xv.y, lo, a1[2 * e]);
            a1[2 * e + 1] = fmaf(xv.y, hi, a1[2 * e + 1]);
        }
    }
    const bool p4 = lane & 16, p3 = lane & 8, p2 = lane & 4;
    float v[8], y[4];
#pragma unroll
    for (int e = 0; e < 8; e++) v[e] = (p4 ? a1[e] : a0[e]) + shx(p4 ? a0[e] : a1[e], 16);
#pragma unroll
    for (int e = 0; e < 4; e++) y[e] = (p3 ? v[4 + e] : v[e]) + shx(p3 ? v[e] : v[4 + e], 8);
    float2 z;
    z.x = (p2 ? y[2] : y[0]) + shx(p2 ? y[0] : y[2], 4);
    z.y = (p2 ? y[3] : y[1]) + shx(p2 ? y[1] : y[3], 4);
    red[(lane & 16) + (lane & 3) * 4 + ((lane >> 3) & 1) * 2 + ((lane >> 2) & 1)] = z;
}

template <int N>
__device__ __forceinline__ void gather(uint4 (&v)[N], const uint4* p, int stride, unsigned sleep_ns) {
    uint32_t n = 0;
    bool ok;
    do {
#pragma unroll
        for (int k = 0; k < N; k++)
            if (!valid4(v[k])) v[k] = ld_poll(p + k * stride);
        ok = true;
#pragma unroll
        for (int k = 0; k < N; k++) ok = ok && valid4(v[k]);
        if (++n > SPIN_LIMIT) __trap();
        if (!ok && sleep_ns) __nanosleep(sleep_ns);
    } while (!ok);
}

enum { NB_Q = 1, NB_F = 2, NB_O = 3, NB_C = 4 };

__global__ void __launch_bounds__(NTHREADS, 1)
fused_decode_kernel(const __nv_bfloat16* __restrict__ x, const __nv_bfloat16* __restrict__ kc,
                    const __nv_bfloat16* __restrict__ vc, const __nv_bfloat16* __restrict__ wq,
                    const __nv_bfloat16* __restrict__ wo, const __nv_bfloat16* __restrict__ wg,
                    const __nv_bfloat16* __restrict__ wu, const __nv_bfloat16* __restrict__ wd,
                    __nv_bfloat16* __restrict__ out) {
    extern __shared__ __align__(1024) unsigned char smem[];
    const uint32_t sb = (uint32_t)__cvta_generic_to_shared(smem);
    const int c = blockIdx.x, g = c >> 4, j = c & 15, b = j >> 3, s = j & 7;
    const int warp = threadIdx.x >> 5, lane = threadIdx.x & 31;
    const uint32_t bars = sb + SM_BAR;
    const bool ffn = c < NFFN;

    if (warp == 0) {
        const size_t off = ((size_t)(b * 8 + g) * SK + (SK - WIN) + s * 512) * DH;
        const char* kp = (const char*)(kc + off);
        const char* vp = (const char*)(vc + off) - (size_t)NT * TILE_BYTES;
        if (lane == 0) STAMP(0);
        if (lane < NBAR) mbar_init(bars + lane * 8, lane < BAR_EMPTY ? 1 : 8);
        asm volatile("fence.mbarrier_init.release.cluster;" ::: "memory");
        __syncwarp();
        uint64_t pol;
        asm volatile("createpolicy.fractional.L2::evict_first.b64 %0, 1.0;" : "=l"(pol));
        if (lane == 0) {
#pragma unroll
            for (int i = 0; i < STAGES; i++) bulk_load(sb + SM_RING + i * TILE_BYTES, kp + i * TILE_BYTES, TILE_BYTES, bars + i * 8, pol);
        }
        __syncthreads();
        if (lane == 0) {
            int slot = 0;
            for (int i = STAGES; i < 2 * NT; i++) {
                mbar_wait(bars + (BAR_EMPTY + i - STAGES) * 8);
                bulk_load(sb + SM_RING + slot * TILE_BYTES, (i < NT ? kp : vp) + (size_t)i * TILE_BYTES, TILE_BYTES, bars + i * 8, pol);
                if (++slot == STAGES) slot = 0;
            }
            if (ffn) bulk_load(sb + SM_WD, wd + (size_t)c * 16 * DM, WD_BYTES, bars + BAR_WD * 8, pol);
            bulk_load(sb + SM_WO, wo + (size_t)c * 32 * DM, WO_BYTES, bars + BAR_WO * 8, pol);
            STAMP(1);
        }
    } else if (warp == 1) {
        {
            uint32_t xw[2][7];
#pragma unroll
            for (int r = 0; r < 2; r++)
#pragma unroll
                for (int i = 0; i < 7; i++) xw[r][i] = __ldg((const uint32_t*)x + r * (DM / 2) + lane + 32 * i);
            float mean[2], den[2];
#pragma unroll
            for (int r = 0; r < 2; r++) {
                float t = 0.f;
#pragma unroll
                for (int i = 0; i < 7; i++) t += bf_lo(xw[r][i]) + bf_hi(xw[r][i]);
#pragma unroll
                for (int m = 16; m; m >>= 1) t += shx(t, m);
                const float mu = t * (1.f / DM);
                float q = 0.f;
#pragma unroll
                for (int i = 0; i < 7; i++) {
                    const float d0 = bf_lo(xw[r][i]) - mu, d1 = bf_hi(xw[r][i]) - mu;
                    q = fmaf(d0, d0, fmaf(d1, d1, q));
                }
#pragma unroll
                for (int m = 16; m; m >>= 1) q += shx(q, m);
                mean[r] = rbf(mu);
                den[r] = rbf(sqrtf(rbf(rbf(q * (1.f / DM)) + 1e-5f)));
            }
            float4* xn4 = (float4*)(smem + SM_XN);
#pragma unroll
            for (int i = 0; i < 7; i++) {
                float4 o;
                o.x = rbf(rbf(bf_lo(xw[0][i]) - mean[0]) / den[0]);
                o.y = rbf(rbf(bf_lo(xw[1][i]) - mean[1]) / den[1]);
                o.z = rbf(rbf(bf_hi(xw[0][i]) - mean[0]) / den[0]);
                o.w = rbf(rbf(bf_hi(xw[1][i]) - mean[1]) / den[1]);
                xn4[lane + 32 * i] = o;
            }
        }
        __syncthreads();
        if (lane == 0) STAMP(2);
        const int ob = c / 56, ocol = (c % 56) * 8 + (lane & 1) + ((lane >> 1) & 1) * 4 + ((lane >> 2) & 1) * 2;
        float xres = 0.f;
        if (ffn && lane < 8) xres = __bfloat162float(x[ob * DM + ocol]);
        const uint4 zero4 = make_uint4(0, 0, 0, 0);
        {
            uint4 v[2] = {zero4, zero4};
            gather<2>(v, (const uint4*)g_q + (b * 8 + g) * 64 + lane, 32, 100);
            ((uint4*)(smem + SM_QS))[lane] = v[0];
            ((uint4*)(smem + SM_QS))[lane + 32] = v[1];
            __syncwarp();
            bar_arrive(NB_Q, 288);
        }
        if (lane == 0) STAMP(3);
        mbar_wait(bars + (NT + 1) * 8);
        {
            uint4 v[1] = {zero4};
            gather<1>(v, g_ml + (c & ~7) + (lane & 7), 0, 200);
            const float m0 = __uint_as_float(v[0].x), m1 = __uint_as_float(v[0].z);
            float M0 = m0, M1 = m1;
#pragma unroll
            for (int m = 1; m < 8; m <<= 1) { M0 = fmaxf(M0, shx(M0, m)); M1 = fmaxf(M1, shx(M1, m)); }
            const float e0 = __expf(m0 - M0), e1 = __expf(m1 - M1);
            float L0 = e0 * __uint_as_float(v[0].y), L1 = e1 * __uint_as_float(v[0].w);
#pragma unroll
            for (int m = 1; m < 8; m <<= 1) { L0 += shx(L0, m); L1 += shx(L1, m); }
            if (lane == s) *(float2*)(smem + SM_ST + 128) = make_float2(e0 / L0, e1 / L1);
            __syncwarp();
            bar_arrive(NB_F, 288);
        }
        if (lane == 0) STAMP(4);
        uint4 vo[8], vf[8];
        uint4* po = g_o + c * 256 + lane;
        uint4* pf = g_f + c * 256 + lane;
        mbar_wait(bars + (2 * NT - 2) * 8);
#pragma unroll
        for (int k = 0; k < 8; k++) vo[k] = ld_poll(po + k * 32);
        if (ffn) {
#pragma unroll
            for (int k = 0; k < 8; k++) vf[k] = ld_poll(pf + k * 32);
        }
        mbar_wait(bars + (2 * NT - 1) * 8);
        if (lane == 0) STAMP(5);
        {
            gather<8>(vo, po, 32, 0);
            float o0[4], o1[4];
            o0[0] = (__uint_as_float(vo[0].x) + __uint_as_float(vo[1].x)) + (__uint_as_float(vo[2].x) + __uint_as_float(vo[3].x));
            o0[1] = (__uint_as_float(vo[0].y) + __uint_as_float(vo[1].y)) + (__uint_as_float(vo[2].y) + __uint_as_float(vo[3].y));
            o0[2] = (__uint_as_float(vo[0].z) + __uint_as_float(vo[1].z)) + (__uint_as_float(vo[2].z) + __uint_as_float(vo[3].z));
            o0[3] = (__uint_as_float(vo[0].w) + __uint_as_float(vo[1].w)) + (__uint_as_float(vo[2].w) + __uint_as_float(vo[3].w));
            o1[0] = (__uint_as_float(vo[4].x) + __uint_as_float(vo[5].x)) + (__uint_as_float(vo[6].x) + __uint_as_float(vo[7].x));
            o1[1] = (__uint_as_float(vo[4].y) + __uint_as_float(vo[5].y)) + (__uint_as_float(vo[6].y) + __uint_as_float(vo[7].y));
            o1[2] = (__uint_as_float(vo[4].z) + __uint_as_float(vo[5].z)) + (__uint_as_float(vo[6].z) + __uint_as_float(vo[7].z));
            o1[3] = (__uint_as_float(vo[4].w) + __uint_as_float(vo[5].w)) + (__uint_as_float(vo[6].w) + __uint_as_float(vo[7].w));
            const bool p4 = lane & 16, p3 = lane & 8;
            __syncwarp();
            const float a0 = (p4 ? o0[2] : o0[0]) + shx(p4 ? o0[0] : o0[2], 16);
            const float a1 = (p4 ? o0[3] : o0[1]) + shx(p4 ? o0[1] : o0[3], 16);
            const float b0 = (p4 ? o1[2] : o1[0]) + shx(p4 ? o1[0] : o1[2], 16);
            const float b1 = (p4 ? o1[3] : o1[1]) + shx(p4 ? o1[1] : o1[3], 16);
            const float r0 = (p3 ? a1 : a0) + shx(p3 ? a0 : a1, 8);
            const float r1 = (p3 ? b1 : b0) + shx(p3 ? b0 : b1, 8);
            ((uint32_t*)(smem + SM_VEC))[((lane >> 1) & 3) * 8 + (lane >> 3) * 2 + (lane & 1)] = pack_bf(r0, r1);
            bar_arrive(NB_O, 256);
        }
        if (lane == 0) STAMP(6);
#pragma unroll
        for (int k = 0; k < 8; k++) po[k * 32] = zero4;
        g_q[((lane >> 4) * 8 + g) * 256 + j * 16 + (lane & 15)] = 0;
        if (lane == 0) g_ml[c] = zero4;
        if (ffn) {
            gather<8>(vf, pf, 32, 0);
            float t[4];
            t[0] = t[1] = t[2] = t[3] = 0.f;
#pragma unroll
            for (int k = 0; k < 8; k++) {
                t[0] += __uint_as_float(vf[k].x); t[1] += __uint_as_float(vf[k].y);
                t[2] += __uint_as_float(vf[k].z); t[3] += __uint_as_float(vf[k].w);
            }
            __syncwarp();
            const bool p1 = lane & 2, p2 = lane & 4;
            const float a0 = (p1 ? t[2] : t[0]) + shx(p1 ? t[0] : t[2], 2);
            const float a1 = (p1 ? t[3] : t[1]) + shx(p1 ? t[1] : t[3], 2);
            float r = (p2 ? a1 : a0) + shx(p2 ? a0 : a1, 4);
            r += shx(r, 8);
            r += shx(r, 16);
            if (lane < 8) out[ob * DM + ocol] = __float2bfloat16_rn(xres + r);
#pragma unroll
            for (int k = 0; k < 8; k++) pf[k * 32] = zero4;
        }
        if (lane == 0) STAMP(7);
    } else {
        const int w = warp - 2, tid = threadIdx.x - 64;
        const int g8 = lane >> 2, t = lane & 3;
        {
            const int r0 = tid >> 2;
            uint4 wv[7], wf[7];
            const __nv_bfloat16* pq = wq + (size_t)r0 * QD + c * 32 + t * 8;
#pragma unroll
            for (int i = 0; i < 7; i++) wv[i] = ldg_nc(pq + (size_t)i * 64 * QD);
            if (ffn) {
                const __nv_bfloat16* pf = ((t & 2) ? wu : wg) + (size_t)r0 * FF + c * 16 + (t & 1) * 8;
#pragma unroll
                for (int i = 0; i < 7; i++) wf[i] = ldg_nc(pf + (size_t)i * 64 * FF);
            }
            __syncthreads();
            const float2* xn = (const float2*)(smem + SM_XN);
            float2* red = (float2*)(smem + SM_RED);
            gemv0(wv, xn, r0, lane, red + w * 32);
            bar_sync(NB_C, 256);
            if (w == 0) {
                float2 a = red[lane];
#pragma unroll
                for (int k = 1; k < 8; k++) { const float2 v = red[k * 32 + lane]; a.x += v.x; a.y += v.y; }
                uint32_t word = pack_bf(a.x, a.y);
                if (word == 0) word = 0x8000u;
                st_pub32(g_q + ((lane >> 4) * 8 + g) * 256 + j * 16 + (lane & 15), word);
                if (lane == 0) STAMP(8);
            }
            if (ffn) {
                gemv0(wf, xn, r0, lane, red + 256 + w * 32);
                bar_sync(NB_C, 256);
                if (w == 1) {
                    float2 a = red[256 + lane];
#pragma unroll
                    for (int k = 1; k < 8; k++) { const float2 v = red[256 + k * 32 + lane]; a.x += v.x; a.y += v.y; }
                    a.x = rbf(a.x); a.y = rbf(a.y);
                    const float u0 = shx(a.x, 8), u1 = shx(a.y, 8);
                    const float h0 = a.x > 0.f ? a.x * u0 : 0.f, h1 = a.y > 0.f ? a.y * u1 : 0.f;
                    const float k0 = shx(h0, 16), k1 = shx(h1, 16);
                    if (lane < 8) *(uint2*)(smem + SM_VEC + 128 + lane * 8) = make_uint2(pack_bf(h0, k0), pack_bf(h1, k1));
                }
            }
        }
        bar_sync(NB_Q, 288);
        {
            const int blk = w & 3, dh = w >> 2;
            uint4 qf[4];
#pragma unroll
            for (int i = 0; i < 4; i++)
                qf[i] = lds128(sb + SM_QS + (g8 & 1) * 512 + (dh * 2 + (i >> 1)) * 128 + 16 * (t + 4 * ((i & 1) ^ ((g8 >> 1) & 1))));
            const uint32_t ko0 = (blk * 16 + g8) * 512 + dh * 256 + 16 * (t + 4 * (g8 & 1));
            const uint32_t ko1 = ko0 ^ 64;
            float2* sp = (float2*)(smem + SM_SP) + dh * 512 + blk * 16 + g8 + (t >> 1) * 8;
            int slot = 0;
            for (int i = 0; i < NT; i++) {
                mbar_wait(bars + i * 8);
                const uint32_t base = sb + SM_RING + slot * TILE_BYTES;
                uint4 X[4], Y[4];
                X[0] = lds128(base + ko0); Y[0] = lds128(base + ko0 + 4096);
                X[1] = lds128(base + ko1); Y[1] = lds128(base + ko1 + 4096);
                X[2] = lds128(base + ko0 + 128); Y[2] = lds128(base + ko0 + 128 + 4096);
                X[3] = lds128(base + ko1 + 128); Y[3] = lds128(base + ko1 + 128 + 4096);
                float c0[4] = {0.f, 0.f, 0.f, 0.f}, c1[4] = {0.f, 0.f, 0.f, 0.f};
#pragma unroll
                for (int k = 0; k < 4; k++) {
                    mma16816(c0, X[k].x, Y[k].x, X[k].y, Y[k].y, qf[k].x, qf[k].y);
                    mma16816(c1, X[k].z, Y[k].z, X[k].w, Y[k].w, qf[k].z, qf[k].w);
                }
                __syncwarp();
                if (lane == 0) mbar_arrive(bars + (BAR_EMPTY + i) * 8);
                if ((t & 1) == (g8 & 1))
                    sp[i * TILE_KEYS] = (t & 2) ? make_float2(c0[2] + c1[2], c0[3] + c1[3]) : make_float2(c0[0] + c1[0], c0[1] + c1[1]);
                if (++slot == STAGES) slot = 0;
            }
        }
        if (tid == 0) STAMP(9);
        bar_sync(NB_C, 256);
        {
            const float4 A = ((const float4*)(smem + SM_SP))[tid], Bv = ((const float4*)(smem + SM_SP))[256 + tid];
            const float s00 = rbf(A.x + Bv.x) * 0.0625f, s01 = rbf(A.y + Bv.y) * 0.0625f;
            const float s10 = rbf(A.z + Bv.z) * 0.0625f, s11 = rbf(A.w + Bv.w) * 0.0625f;
            float m0 = fmaxf(s00, s10), m1 = fmaxf(s01, s11);
#pragma unroll
            for (int m = 16; m; m >>= 1) { m0 = fmaxf(m0, shx(m0, m)); m1 = fmaxf(m1, shx(m1, m)); }
            float2* st = (float2*)(smem + SM_ST);
            if (lane == 0) st[w] = make_float2(m0, m1);
            bar_sync(NB_C, 256);
#pragma unroll
            for (int k = 0; k < 8; k++) { const float2 v = st[k]; m0 = fmaxf(m0, v.x); m1 = fmaxf(m1, v.y); }
            const float p00 = __expf(s00 - m0), p01 = __expf(s01 - m1), p10 = __expf(s10 - m0), p11 = __expf(s11 - m1);
            ((uint2*)(smem + SM_PW))[tid] = make_uint2(pack_bf(p00, p01), pack_bf(p10, p11));
            float l0 = p00 + p10, l1 = p01 + p11;
#pragma unroll
            for (int m = 16; m; m >>= 1) { l0 += shx(l0, m); l1 += shx(l1, m); }
            if (lane == 0) st[8 + w] = make_float2(l0, l1);
            bar_sync(NB_C, 256);
            if (tid == 0) {
                l0 = l1 = 0.f;
#pragma unroll
                for (int k = 0; k < 8; k++) { const float2 v = st[8 + k]; l0 += v.x; l1 += v.y; }
                st_pub(g_ml + c, make_uint4(nz(m0), nz(l0), nz(m1), nz(l1)));
            }
        }
        const int a = g8 >> 1, e = g8 & 1;
        const uint32_t sel0 = a != t ? 0x4444u : (e ? 0x1044u : 0x4410u);
        const uint32_t sel1 = a != t ? 0x4444u : (e ? 0x3244u : 0x4432u);
        const int chunk = 2 * (t ^ a) + (a & 1);
        float acc[4][4];
#pragma unroll
        for (int u = 0; u < 4; u++) acc[u][0] = acc[u][1] = acc[u][2] = acc[u][3] = 0.f;
        {
            const int seg = w & 3, half = w >> 2;
            const uint32_t vo = (half * 32 + 8 * t) * 512 + seg * 128 + 16 * (g8 ^ (2 * t));
            const uint32_t po = sb + SM_PW + (half * 32 + 8 * t) * 4;
            int slot = NT % STAGES;
            for (int i = 0; i < NT; i++) {
                const uint4 P0 = lds128(po + i * TILE_KEYS * 4), P1 = lds128(po + i * TILE_KEYS * 4 + 16);
                mbar_wait(bars + (NT + i) * 8);
                const uint32_t base = sb + SM_RING + slot * TILE_BYTES + vo;
                uint4 X[8];
#pragma unroll
                for (int k = 0; k < 8; k++) X[k] = lds128(base + k * 512);
                vm_step(acc, X[0], X[1], P0.x, P0.y, sel0, sel1);
                vm_step(acc, X[2], X[3], P0.z, P0.w, sel0, sel1);
                vm_step(acc, X[4], X[5], P1.x, P1.y, sel0, sel1);
                vm_step(acc, X[6], X[7], P1.z, P1.w, sel0, sel1);
                if (i < NT - STAGES) {
                    __syncwarp();
                    if (lane == 0) mbar_arrive(bars + (BAR_EMPTY + NT + i) * 8);
                }
                if (++slot == STAGES) slot = 0;
            }
            if (tid == 0) STAMP(10);
            float r[4];
            vm_reduce(acc, r, a);
            bar_sync(NB_F, 288);
            const float f = ((const float*)(smem + SM_ST + 128))[a >> 1];
            uint4* dst = g_o + (g * 16 + (a >> 1) * 8 + seg * 2 + (chunk >> 2)) * 256 + (j * 2 + half) * 8 + (chunk & 3) * 2 + e;
            st_pub(dst, make_uint4(nz(r[0] * f), nz(r[1] * f), nz(r[2] * f), nz(r[3] * f)));
            if (tid == 0) STAMP(11);
        }
        if (w < 7) {
#pragma unroll
            for (int u = 0; u < 4; u++) acc[u][0] = acc[u][1] = acc[u][2] = acc[u][3] = 0.f;
            const uint32_t co = w * 128 + 16 * (g8 ^ (2 * t));
            if (ffn) {
                const uint4 H = lds128(sb + SM_VEC + 128 + t * 16);
                mbar_wait(bars + BAR_WD * 8);
                const uint32_t base = sb + SM_WD + 4 * t * (DM * 2) + co;
                uint4 X[4];
#pragma unroll
                for (int k = 0; k < 4; k++) X[k] = lds128(base + k * (DM * 2));
                vm_step(acc, X[0], X[1], H.x, H.y, sel0, sel1);
                vm_step(acc, X[2], X[3], H.z, H.w, sel0, sel1);
            }
            mbar_wait(bars + BAR_WO * 8);
            if (tid == 0) STAMP(12);
            const uint32_t base = sb + SM_WO + 8 * t * (DM * 2) + co;
            uint4 X[8];
#pragma unroll
            for (int k = 0; k < 8; k++) X[k] = lds128(base + k * (DM * 2));
            bar_sync(NB_O, 256);
            const uint4 O0 = lds128(sb + SM_VEC + t * 32), O1 = lds128(sb + SM_VEC + t * 32 + 16);
            vm_step(acc, X[0], X[1], O0.x, O0.y, sel0, sel1);
            vm_step(acc, X[2], X[3], O0.z, O0.w, sel0, sel1);
            vm_step(acc, X[4], X[5], O1.x, O1.y, sel0, sel1);
            vm_step(acc, X[6], X[7], O1.z, O1.w, sel0, sel1);
            float r[4];
            vm_reduce(acc, r, a);
            st_pub(g_f + ((a >> 1) * 56 + w * 8 + chunk) * 256 + c * 2 + e, make_uint4(nz(r[0]), nz(r[1]), nz(r[2]), nz(r[3])));
            if (tid == 0) STAMP(13);
        }
    }
}

}

extern "C" void kernel_launch(void* const* d_in, const int* in_sizes, int n_in, void* d_out, int out_size) {
    (void)in_sizes; (void)n_in; (void)out_size;
    static bool attr_set = false;
    if (!attr_set) {
        cudaFuncSetAttribute(fused_decode_kernel, cudaFuncAttributeMaxDynamicSharedMemorySize, SM_TOTAL);
        attr_set = true;
    }
    typedef const __nv_bfloat16* P;
    fused_decode_kernel<<<NCTA, NTHREADS, SM_TOTAL>>>((P)d_in[0], (P)d_in[1], (P)d_in[2], (P)d_in[3], (P)d_in[4],
                                                      (P)d_in[6], (P)d_in[7], (P)d_in[8], (__nv_bfloat16*)d_out);
}
```

```cpp
#include <cuda_runtime.h>
#include <cuda.h>
#include <cuda_bf16.h>
#include <stdint.h>

namespace {

constexpr int DM = 448, FF = 1792, SK = 32768, WIN = 4096, DH = 256, QD = 4096;
constexpr int NCTA = 128, NTHREADS = 13 * 32;
constexpr uint32_t SPIN_LIMIT = 1u << 20;

constexpr int TILE_BYTES = 16384, NT = 16, RING = 12;
constexpr int T_K0 = 2, T_F0 = 8, T_F1 = 11, T_V = 4 + NT, T_WD = T_V + NT, T_WO = T_WD + 2, NTILE = T_WO + 4;
constexpr int HALF_BYTES = 224 * 64, WD_BYTES = 224 * 32, WO_BYTES = 256 * 32;
constexpr int W1 = 3, WMIN = 2, WMAX = 5, WMAX_FROM = 10;
constexpr uint32_t T0 = 1400, TAU_K = 620, TAU_V = 640, TAU_W = 290, T_SHIFT = 400;
constexpr int STAGGER = 24;

constexpr int SM_RING = 0;
constexpr int SM_P = SM_RING + RING * TILE_BYTES;
constexpr int SM_QS = SM_P + 16384;
constexpr int SM_X = SM_QS + 1024;
constexpr int SM_XN = SM_X + 1792;
constexpr int SM_RED = SM_XN + 1792;
constexpr int SM_ST = SM_RED + 4096;
constexpr int SM_BAR = SM_ST + 256;
constexpr int BAR_EMPTY = NTILE, NEMPTY = NTILE - RING, NBAR = NTILE + NEMPTY, BAR_X = NBAR;
constexpr int SM_TOTAL = SM_BAR + (NBAR + 2) * 8;
static_assert(NEMPTY > T_V + 2 && NEMPTY <= T_WD && T_F1 < RING && SM_TOTAL <= 232448, "layout");

constexpr int MB_S = 0, MB_O = 128, MB_H = 136, MB_SIZE = 144;
__device__ __align__(128) uint32_t g_q[16 * 256];
__device__ __align__(128) uint4 g_r[84 * 2];
__device__ __align__(128) uint4 g_mb[NCTA * MB_SIZE];

__device__ __forceinline__ void mbar_init(uint32_t bar, uint32_t cnt) {
    asm volatile("mbarrier.init.shared::cta.b64 [%0], %1;" ::"r"(bar), "r"(cnt) : "memory");
}
__device__ __forceinline__ void mbar_expect(uint32_t bar, uint32_t bytes) {
    asm volatile("mbarrier.arrive.expect_tx.shared::cta.b64 _, [%0], %1;" ::"r"(bar), "r"(bytes) : "memory");
}
__device__ __forceinline__ void mbar_arrive(uint32_t bar) {
    asm volatile("mbarrier.arrive.shared::cta.b64 _, [%0];" ::"r"(bar) : "memory");
}
__device__ __forceinline__ void mbar_wait(uint32_t bar) {
    uint32_t done, n = 0;
#pragma unroll 1
    do {
        asm volatile("{\n.reg .pred p;\nmbarrier.try_wait.parity.shared::cta.b64 p, [%1], 0;\nselp.u32 %0, 1, 0, p;\n}"
                     : "=r"(done) : "r"(bar) : "memory");
        if (++n > SPIN_LIMIT) __trap();
    } while (!done);
}
__device__ __forceinline__ bool mbar_test(uint32_t bar) {
    uint32_t done;
    asm volatile("{\n.reg .pred p;\nmbarrier.test_wait.parity.shared::cta.b64 p, [%1], 0;\nselp.u32 %0, 1, 0, p;\n}"
                 : "=r"(done) : "r"(bar) : "memory");
    return done;
}
__device__ __forceinline__ uint32_t now_ns() {
    uint32_t t;
    asm volatile("mov.u32 %0, %%globaltimer_lo;" : "=r"(t));
    return t;
}
__device__ __forceinline__ void mbar_wait_until(uint32_t bar, uint32_t deadline) {
#pragma unroll 1
    for (uint32_t n = 0; n < SPIN_LIMIT; n++) {
        const int32_t left = (int32_t)(deadline - now_ns());
        if (left <= 0) break;
        if (left > 100) {
            if (mbar_test(bar)) break;
            __nanosleep(20);
        }
    }
}
__device__ __forceinline__ void bulk_load(uint32_t dst, const void* src, uint32_t bytes, uint32_t bar, uint64_t pol) {
    asm volatile("cp.async.bulk.shared::cluster.global.mbarrier::complete_tx::bytes.L2::cache_hint [%0], [%1], %2, [%3], %4;"
                 ::"r"(dst), "l"(src), "r"(bytes), "r"(bar), "l"(pol) : "memory");
}
__device__ __forceinline__ void tensor_load(uint32_t dst, const CUtensorMap* map, int col, int row, uint32_t bar, uint64_t pol) {
    asm volatile("cp.async.bulk.tensor.2d.shared::cluster.global.mbarrier::complete_tx::bytes.L2::cache_hint [%0], [%1, {%2, %3}], [%4], %5;"
                 ::"r"(dst), "l"(map), "r"(col), "r"(row), "r"(bar), "l"(pol) : "memory");
}
__device__ __forceinline__ void pin(uint32_t& v) { asm volatile("" : "+r"(v)); }
__device__ __forceinline__ void pin(float& v) { asm volatile("" : "+f"(v)); }
__device__ __forceinline__ void pin2(uint32_t& v) { v = __shfl_xor_sync(0xffffffffu, v, 0); }
template <class T> __device__ __forceinline__ void pin2(T*& p) { p = (T*)__shfl_xor_sync(0xffffffffu, (unsigned long long)p, 0); }
__device__ __forceinline__ void bar_sync(int id, int n) { asm volatile("bar.sync %0, %1;" ::"r"(id), "r"(n) : "memory"); }
__device__ __forceinline__ void bar_arrive(int id, int n) { asm volatile("bar.arrive %0, %1;" ::"r"(id), "r"(n) : "memory"); }
__device__ __forceinline__ uint4 lds128(uint32_t a) {
    uint4 v;
    asm volatile("ld.shared.v4.u32 {%0,%1,%2,%3}, [%4];" : "=r"(v.x), "=r"(v.y), "=r"(v.z), "=r"(v.w) : "r"(a) : "memory");
    return v;
}
__device__ __forceinline__ float2 lds64f(uint32_t a) {
    float2 v;
    asm volatile("ld.shared.v2.f32 {%0,%1}, [%2];" : "=f"(v.x), "=f"(v.y) : "r"(a) : "memory");
    return v;
}
__device__ __forceinline__ void sts32f(uint32_t a, float v) { asm volatile("st.shared.f32 [%0], %1;" ::"r"(a), "f"(v) : "memory"); }
__device__ __forceinline__ uint4 ldsm_t(uint32_t a) {
    uint4 v;
    asm volatile("ldmatrix.sync.aligned.m8n8.x4.trans.shared.b16 {%0,%1,%2,%3}, [%4];"
                 : "=r"(v.x), "=r"(v.y), "=r"(v.z), "=r"(v.w) : "r"(a) : "memory");
    return v;
}
__device__ __forceinline__ uint4 ld_poll(const uint4* p) {
    uint4 v;
    asm volatile("ld.relaxed.gpu.global.v4.u32 {%0,%1,%2,%3}, [%4];" : "=r"(v.x), "=r"(v.y), "=r"(v.z), "=r"(v.w) : "l"(p) : "memory");
    return v;
}
__device__ __forceinline__ uint2 ld_poll64(const uint2* p) {
    uint2 v;
    asm volatile("ld.relaxed.gpu.global.v2.u32 {%0,%1}, [%2];" : "=r"(v.x), "=r"(v.y) : "l"(p) : "memory");
    return v;
}
__device__ __forceinline__ uint32_t ld_poll32(const uint32_t* p) {
    uint32_t v;
    asm volatile("ld.relaxed.gpu.global.u32 %0, [%1];" : "=r"(v) : "l"(p) : "memory");
    return v;
}
__device__ __forceinline__ void st_pub(uint4* p, uint4 v) {
    asm volatile("st.relaxed.gpu.global.v4.u32 [%0], {%1,%2,%3,%4};" ::"l"(p), "r"(v.x), "r"(v.y), "r"(v.z), "r"(v.w) : "memory");
}
__device__ __forceinline__ void st_pub64(void* p, uint32_t a, uint32_t b) {
    asm volatile("st.relaxed.gpu.global.v2.u32 [%0], {%1,%2};" ::"l"(p), "r"(a), "r"(b) : "memory");
}
__device__ __forceinline__ void st_pub32(uint32_t* p, uint32_t v) {
    asm volatile("st.relaxed.gpu.global.u32 [%0], %1;" ::"l"(p), "r"(v) : "memory");
}
__device__ __forceinline__ uint32_t confirm_store(const void* p) {
    uint32_t v;
    asm volatile("atom.relaxed.gpu.global.exch.b32 %0, [%1], 0;" : "=r"(v) : "l"(p) : "memory");
    return v;
}
__device__ __forceinline__ uint32_t min4(const uint4& v) { return min(min(v.x, v.y), min(v.z, v.w)); }
__device__ __forceinline__ uint32_t nzw(uint32_t w) { return w == 0 ? 0x8000u : w; }
__device__ __forceinline__ void mma(float (&c)[4], const uint4& a, uint32_t b0, uint32_t b1) {
    asm volatile("mma.sync.aligned.m16n8k16.row.col.f32.bf16.bf16.f32 {%0,%1,%2,%3}, {%4,%5,%6,%7}, {%8,%9}, {%0,%1,%2,%3};"
                 : "+f"(c[0]), "+f"(c[1]), "+f"(c[2]), "+f"(c[3]) : "r"(a.x), "r"(a.y), "r"(a.z), "r"(a.w), "r"(b0), "r"(b1));
}
__device__ __forceinline__ float bf_lo(uint32_t w) { return __uint_as_float(w << 16); }
__device__ __forceinline__ float bf_hi(uint32_t w) { return __uint_as_float(w & 0xffff0000u); }
__device__ __forceinline__ float rbf(float f) { return __bfloat162float(__float2bfloat16_rn(f)); }
__device__ __forceinline__ uint32_t pack_bf(float lo, float hi) {
    uint32_t r;
    asm("cvt.rn.bf16x2.f32 %0, %1, %2;" : "=r"(r) : "f"(hi), "f"(lo));
    return r;
}
__device__ __forceinline__ float ex2(float v) {
    float r;
    asm("ex2.approx.ftz.f32 %0, %1;" : "=f"(r) : "f"(v));
    return r;
}
__device__ __forceinline__ float shx(float v, int m) { return __shfl_xor_sync(0xffffffffu, v, m); }

__device__ __forceinline__ void gemv0(uint32_t waddr, int step, uint32_t xaddr, int g8, int t, float* red) {
    const uint32_t lo = (g8 & 1) ? 0x1044u : 0x4410u, hi = (g8 & 1) ? 0x3244u : 0x4432u;
    const uint32_t s0 = (g8 & 2) ? 0x4444u : lo, s1 = (g8 & 2) ? 0x4444u : hi;
    const uint32_t s2 = (g8 & 2) ? lo : 0x4444u, s3 = (g8 & 2) ? hi : 0x4444u;
    float c0[4] = {0.f, 0.f, 0.f, 0.f}, c1[4] = {0.f, 0.f, 0.f, 0.f};
#pragma unroll
    for (int i = 0; i < 7; i++) {
        const uint4 X = lds128(waddr + i * step);
        uint32_t xw;
        asm volatile("ld.shared.u32 %0, [%1];" : "=r"(xw) : "r"(xaddr + i * 16) : "memory");
        const uint4 a = make_uint4(__byte_perm(xw, 0, s0), __byte_perm(xw, 0, s1), __byte_perm(xw, 0, s2), __byte_perm(xw, 0, s3));
        mma(c0, a, X.x, X.y);
        mma(c1, a, X.z, X.w);
    }
    red[(g8 >> 2) * 32 + 8 * t + (g8 & 3)] = c0[0] + c0[3];
    red[(g8 >> 2) * 32 + 8 * t + (g8 & 3) + 4] = c1[0] + c1[3];
}

__device__ __forceinline__ void gather2(uint4& v0, uint4& v1, const uint4* p0, const uint4* p1, unsigned sleep_ns) {
    uint32_t n = 0;
#pragma unroll 1
    while (true) {
        v0 = ld_poll(p0);
        v1 = ld_poll(p1);
        if (__all_sync(0xffffffffu, min(min4(v0), min4(v1)) != 0)) break;
        if (++n > SPIN_LIMIT) __trap();
        __nanosleep(sleep_ns);
    }
}

enum { NB_R = 1, NB_A = 2, NB_E = 3, NB_X = 4, NB_P0 = 5, NB_P1 = 6 };

struct Maps { CUtensorMap v, wq, wg, wu, wo, wd; };

__global__ void __launch_bounds__(NTHREADS, 1)
fused_decode_kernel(const __nv_bfloat16* __restrict__ x, const __nv_bfloat16* __restrict__ kc,
                    __nv_bfloat16* __restrict__ out, const __grid_constant__ Maps maps) {
    extern __shared__ __align__(1024) unsigned char smem[];
    const uint32_t sb = (uint32_t)__cvta_generic_to_shared(smem);
    const int c = blockIdx.x, g = c >> 4, j = c & 15, b = j >> 3, s = j & 7;
    const uint32_t bars = sb + SM_BAR;
    const int row0 = (b * 8 + g) * SK + (SK - WIN);
    {
        const uint32_t off = (uint32_t)(row0 + s * 32) * (DH * 2) + (TILE_BYTES - 128) - threadIdx.x * 128;
        asm volatile("{ .reg .pred p; .reg .u64 a; cvt.u64.u32 a, %1; add.u64 a, a, %0; setp.lt.u32 p, %2, 128; @p prefetch.global.L2 [a]; }"
                     ::"l"(kc), "r"(off), "r"(threadIdx.x) : "memory");
    }
    const int warp = __shfl_sync(0xffffffffu, threadIdx.x >> 5, 0), lane = threadIdx.x & 31;
    const bool proj = s < 7;
    const int cbk = (g & 1) * 14 + 2 * s + b, rbk = g >> 1;

    if (warp == 0) {
        const char* kp = (const char*)kc + (size_t)(row0 + s * 32) * (DH * 2);
        uint64_t pol;
        asm volatile("createpolicy.fractional.L2::evict_first.b64 %0, 1.0;" : "=l"(pol));
        if (lane == 0) {
            *(volatile uint32_t*)(smem + SM_ST + 240) = now_ns();
            mbar_init(bars + T_K0 * 8, 1);
            mbar_expect(bars + T_K0 * 8, TILE_BYTES);
            bulk_load(sb + SM_RING + T_K0 * TILE_BYTES, kp, TILE_BYTES, bars + T_K0 * 8, pol);
#pragma unroll
            for (int i = 0; i < 2; i++) {
                mbar_init(bars + i * 8, 1);
                mbar_expect(bars + i * 8, HALF_BYTES);
                tensor_load(sb + SM_RING + i * TILE_BYTES, &maps.wq, c * 32, i * 224, bars + i * 8, pol);
            }
        }
        __syncwarp();
        bar_sync(0, NTHREADS);
        if (lane == 0) {
            uint32_t dst = sb + SM_RING + W1 * TILE_BYTES, bar = bars + W1 * 8;
            const int stag = (2 * g - 7) * STAGGER;
            uint32_t deadline = *(volatile uint32_t*)(smem + SM_ST + 240) + T0 + stag;
            auto ready = [&](int i, uint32_t bytes) {
                if (i >= RING) mbar_wait(bar + (BAR_EMPTY - RING) * 8);
                if (i >= WMAX_FROM && i < T_WD && !mbar_test(bar - WMAX * 8)) {
                    mbar_wait(bar - WMAX * 8);
                    const uint32_t t = now_ns() + T_SHIFT;
                    if ((int32_t)(t - deadline) > 0) deadline = t;
                }
                mbar_expect(bar, bytes);
                mbar_wait_until(bar - WMIN * 8, deadline);
            };
            auto next = [&](uint32_t tau) {
                deadline += tau;
                bar += 8;
                dst += TILE_BYTES;
                if (dst == sb + SM_RING + RING * TILE_BYTES) dst = sb + SM_RING;
            };
#pragma unroll 1
            for (int i = W1; i < T_V; i++) {
                if (i == T_F0 || i == T_F1) {
                    ready(i, proj ? HALF_BYTES : 0);
                    if (proj) {
                        tensor_load(dst, &maps.wg, (rbk * 28 + cbk) * 16, i == T_F0 ? 0 : 224, bar, pol);
                        tensor_load(dst + HALF_BYTES / 2, &maps.wu, (rbk * 28 + cbk) * 16, i == T_F0 ? 0 : 224, bar, pol);
                    }
                    if (i == T_F1) {
                        asm volatile("prefetch.tensormap [%0];" ::"l"(&maps.v) : "memory");
                        asm volatile("prefetch.tensormap [%0];" ::"l"(&maps.wd) : "memory");
                        asm volatile("prefetch.tensormap [%0];" ::"l"(&maps.wo) : "memory");
                    }
                } else {
                    kp += 8 * TILE_BYTES;
                    ready(i, TILE_BYTES);
                    bulk_load(dst, kp, TILE_BYTES, bar, pol);
                }
                next(TAU_K);
            }
#pragma unroll 1
            for (int i = T_V; i < T_WD; i++) {
                ready(i, TILE_BYTES);
                tensor_load(dst, &maps.v, s * 32, row0 + (i - T_V) * 256, bar, pol);
                next(TAU_V);
                if (i == T_WD - 3 || i == T_WD - 2) deadline -= stag / 2;
            }
            if (proj) {
#pragma unroll 1
                for (int i = T_WD; i < NTILE; i++) {
                    const bool wd = i < T_WO;
                    ready(i, wd ? WD_BYTES : WO_BYTES);
                    tensor_load(dst, wd ? &maps.wd : &maps.wo, cbk * 16,
                                wd ? rbk * 448 + (i - T_WD) * 224 : rbk * 1024 + (i - T_WO) * 256, bar, pol);
                    next(TAU_W);
                }
            }
        }
    } else if (warp < 5) {
        const int w = warp - 1;
        const int g8 = lane >> 2, t = lane & 3;
        if (w < 2) {
            if (lane == 0) {
                mbar_init(bars + (BAR_X + w) * 8, 1);
                mbar_expect(bars + (BAR_X + w) * 8, DM * 2);
                asm volatile("cp.async.bulk.shared::cluster.global.mbarrier::complete_tx::bytes [%0], [%1], %2, [%3];"
                             ::"r"(sb + SM_X + w * DM * 2), "l"(x + w * DM), "r"(DM * 2), "r"(bars + (BAR_X + w) * 8) : "memory");
            }
            __syncwarp();
            bar_arrive(0, NTHREADS);
            mbar_wait(bars + (BAR_X + w) * 8);
            uint32_t xw[7];
#pragma unroll
            for (int i = 0; i < 7; i++) xw[i] = ((const uint32_t*)(smem + SM_X))[w * (DM / 2) + lane + 32 * i];
            float sum = 0.f;
#pragma unroll
            for (int i = 0; i < 7; i++) sum += bf_lo(xw[i]) + bf_hi(xw[i]);
#pragma unroll
            for (int m = 16; m; m >>= 1) sum += shx(sum, m);
            const float mu = sum * (1.f / DM);
            float q = 0.f;
#pragma unroll
            for (int i = 0; i < 7; i++) {
                const float d0 = bf_lo(xw[i]) - mu, d1 = bf_hi(xw[i]) - mu;
                q = fmaf(d0, d0, fmaf(d1, d1, q));
            }
#pragma unroll
            for (int m = 16; m; m >>= 1) q += shx(q, m);
            const float mean = rbf(mu);
            const float inv = 1.f / rbf(sqrtf(rbf(rbf(q * (1.f / DM)) + 1e-5f)));
#pragma unroll
            for (int i = 0; i < 7; i++)
                ((uint32_t*)(smem + SM_XN))[w * (DM / 2) + lane + 32 * i] =
                    pack_bf(rbf(bf_lo(xw[i]) - mean) * inv, rbf(bf_hi(xw[i]) - mean) * inv);
            bar_arrive(NB_X, 320);
        } else if (w == 2) {
            bar_sync(0, NTHREADS);
            const uint4* pq = (const uint4*)g_q + (b * 8 + g) * 64 + lane;
            uint4 v0, v1;
            gather2(v0, v1, pq, pq + 32, 50);
            ((uint4*)(smem + SM_QS))[lane] = v0;
            ((uint4*)(smem + SM_QS))[lane + 32] = v1;
        } else {
            bar_sync(0, NTHREADS);
            bar_sync(NB_R, 288);
            const float2* red = (const float2*)(smem + SM_RED);
            float2 a = red[lane];
#pragma unroll
            for (int k = 1; k < 8; k++) { const float2 v = red[k * 32 + lane]; a.x += v.x; a.y += v.y; }
            st_pub32(g_q + ((lane >> 4) * 8 + g) * 256 + j * 16 + (lane & 15), nzw(pack_bf(a.x, a.y)));
        }
        __syncwarp();
        bar_sync(NB_A, 128);
        int slot = T_K0;
        {
            uint32_t qf[8][2];
#pragma unroll
            for (int k = 0; k < 8; k++) {
                const uint32_t* qw = (const uint32_t*)(smem + SM_QS) + (g8 & 1) * 128 +
                                     ((k >> 1) * 8 + t + 4 * ((k & 1) ^ (g8 >> 2))) * 4 + ((g8 >> 1) & 1);
                qf[k][0] = qw[0];
                qf[k][1] = qw[2];
            }
            uint32_t ko0 = sb + SM_RING + (w * 8 + g8) * 512 + 16 * (t + 4 * (g8 & 1));
            uint32_t ko1 = ko0 ^ 64;
            pin(ko0); pin(ko1);
            uint32_t keep0 = 0, keep1 = 0;
            int pos = T_K0;
#pragma unroll 1
            for (int i = 0; i < NT; i++) {
                const uint32_t b0 = ko0 + slot * TILE_BYTES, b1 = ko1 + slot * TILE_BYTES;
                mbar_wait(bars + pos * 8);
                uint4 X[8];
#pragma unroll
                for (int k = 0; k < 4; k++) { X[2 * k] = lds128(b0 + k * 128); X[2 * k + 1] = lds128(b1 + k * 128); }
                float c0[4] = {0.f, 0.f, 0.f, 0.f}, c1[4] = {0.f, 0.f, 0.f, 0.f};
#pragma unroll
                for (int k = 0; k < 4; k++) {
                    mma(c0, X[2 * k], qf[2 * k][0], qf[2 * k][1]);
                    mma(c1, X[2 * k + 1], qf[2 * k + 1][0], qf[2 * k + 1][1]);
                }
                __syncwarp();
                if (lane == 0) mbar_arrive(bars + (BAR_EMPTY + pos) * 8);
                float s0 = (t & 1) ? c0[2] + c1[2] : c0[0] + c1[0], s1 = (t & 1) ? c0[3] + c1[3] : c0[1] + c1[1];
                s0 += shx(s0, 1);
                s1 += shx(s1, 1);
                const uint32_t word = __shfl_sync(0xffffffffu, nzw(pack_bf(s0, s1)), (lane & ~3) + 2 * (g8 & 1));
                if (((i >> 1) & 3) == t) { if (i & 1) keep1 = word; else keep0 = word; }
                if ((i & 7) == 7) st_pub64((uint2*)(g_mb + c * MB_SIZE + MB_S) + (i >> 3) * 128 + w * 32 + lane, keep0, keep1);
                do { pos++; if (++slot == RING) slot = 0; } while (pos == T_F0 || pos == T_F1);
            }
        }
        float acc[4][4];
#pragma unroll
        for (int u = 0; u < 4; u++) acc[u][0] = acc[u][1] = acc[u][2] = acc[u][3] = 0.f;
        uint32_t vo = sb + SM_RING + w * 4096 + ((lane & 7) + 8 * (lane >> 4)) * 64 + 16 * (((lane >> 3) & 1) ^ ((lane >> 1) & 3));
        uint32_t po = sb + SM_P + ((w * 2 + (g8 >> 2)) * 4 + t) * 32;
        uint32_t ro = sb + SM_RED + (w * 64 + 16 * t + g8) * 4, rl = sb + SM_RED + lane * 8, odd = t & 1;
        uint32_t* dsto = (uint32_t*)(g_mb + c * MB_SIZE + MB_O) + (lane & 16) + (lane & 3) * 4 + ((lane >> 2) & 3);
        pin(vo); pin(po); pin2(ro); pin2(rl); pin2(odd); pin2(dsto);
        float inv_l = 0.f;
#pragma unroll 1
        for (int i = 0; i < NT; i++) {
            if (i == 0) bar_sync(NB_P0, 384);
            if (i == 8) {
                bar_sync(NB_P1, 384);
                const float f = ((const float*)(smem + SM_ST + 192))[t >> 1];
#pragma unroll
                for (int u = 0; u < 4; u++) { acc[u][0] *= f; acc[u][2] *= f; }
                float l = 0.f;
#pragma unroll
                for (int k = 0; k < 8; k++) l += ((const float*)(smem + SM_ST + 128))[2 * k + (lane >> 4)];
                inv_l = 1.f / l;
            }
            const uint4 P0 = lds128(po + i * 1024), P1 = lds128(po + i * 1024 + 16);
            uint32_t b0 = vo + slot * TILE_BYTES, b1 = b0 ^ 32;
            pin(b0); pin(b1);
            mbar_wait(bars + (T_V + i) * 8);
            uint4 X[8];
#pragma unroll
            for (int k = 0; k < 4; k++) { X[2 * k] = ldsm_t(b0 + k * 1024); X[2 * k + 1] = ldsm_t(b1 + k * 1024); }
            mma(acc[0], X[0], P0.x, P0.y); mma(acc[1], X[1], P0.x, P0.y);
            mma(acc[2], X[2], P0.z, P0.w); mma(acc[3], X[3], P0.z, P0.w);
            mma(acc[0], X[4], P1.x, P1.y); mma(acc[1], X[5], P1.x, P1.y);
            mma(acc[2], X[6], P1.z, P1.w); mma(acc[3], X[7], P1.z, P1.w);
            if (T_V + i < NEMPTY) {
                __syncwarp();
                if (lane == 0) mbar_arrive(bars + (BAR_EMPTY + T_V + i) * 8);
            }
            if (++slot == RING) slot = 0;
        }
        sts32f(ro, odd ? acc[1][0] + acc[3][0] : acc[0][0] + acc[2][0]);
        sts32f(ro + 32, odd ? acc[1][2] + acc[3][2] : acc[0][2] + acc[2][2]);
        if (w != 0) {
            bar_arrive(NB_A, 128);
        } else {
            bar_sync(NB_A, 128);
            const float2 v0 = lds64f(rl), v1 = lds64f(rl + 256), v2 = lds64f(rl + 512), v3 = lds64f(rl + 768);
            st_pub32(dsto, nzw(pack_bf(((v0.x + v1.x) + (v2.x + v3.x)) * inv_l, ((v0.y + v1.y) + (v2.y + v3.y)) * inv_l)));
        }
    } else {
        const int w = warp - 5, tid = threadIdx.x - 160;
        const int g8 = lane >> 2, t = lane & 3;
        {
            if (lane == 0) {
#pragma unroll
                for (int k = 0; k < (NBAR - W1 + 7) / 8; k++) {
                    const int i = W1 + w + 8 * k;
                    if (i < NBAR) mbar_init(bars + i * 8, i < BAR_EMPTY ? 1 : 4);
                }
                asm volatile("fence.mbarrier_init.release.cluster;" ::: "memory");
            }
            __syncwarp();
            bar_sync(0, NTHREADS);
            uint4* mb = g_mb + c * MB_SIZE + tid;
            if (tid < MB_SIZE) st_pub(mb, make_uint4(0, 0, 0, 0));
            const uint32_t back = tid < MB_SIZE && !(tid & 1) ? confirm_store(mb) : 0;
            bar_sync(NB_X, 320);
            const uint32_t xaddr = sb + SM_XN + (g8 >> 2) * (DM * 2) + (w * 28 + t) * 4;
            const int row = (w & 3) * 56 + 2 * t + (g8 & 1);
            float* redf = (float*)(smem + SM_RED);
            const float2* red = (const float2*)redf;
            const int tq = w >> 2, tf = w >> 2 ? T_F1 : T_F0;
            mbar_wait(bars + tq * 8);
            gemv0(sb + SM_RING + tq * TILE_BYTES + row * 64 + 16 * ((g8 >> 1) ^ t), 512, xaddr, g8, t, redf + w * 64);
            if (back != 0) __trap();
            __syncwarp();
            if (lane == 0) mbar_arrive(bars + (BAR_EMPTY + tq) * 8);
            bar_arrive(NB_R, 288);
            if (proj) {
                mbar_wait(bars + tf * 8);
                gemv0(sb + SM_RING + tf * TILE_BYTES + (g8 >> 2) * (HALF_BYTES / 2) + row * 32 + 16 * (((g8 >> 1) & 1) ^ (t >> 1)),
                      256, xaddr, g8, t, redf + 512 + w * 64);
            }
            __syncwarp();
            if (lane == 0) mbar_arrive(bars + (BAR_EMPTY + tf) * 8);
            if (proj) {
                bar_sync(NB_E, 256);
                if (w == 1) {
                    float2 a = red[256 + lane];
#pragma unroll
                    for (int k = 1; k < 8; k++) { const float2 v = red[256 + k * 32 + lane]; a.x += v.x; a.y += v.y; }
                    a.x = rbf(a.x); a.y = rbf(a.y);
                    const float u0 = shx(a.x, 8), u1 = shx(a.y, 8);
                    const float h0 = (a.x * (a.x > 0.f ? 1.f : 0.f)) * u0, h1 = (a.y * (a.y > 0.f ? 1.f : 0.f)) * u1;
                    if (!(lane & 8))
                        st_pub32((uint32_t*)(g_mb + c * MB_SIZE + MB_H) + (lane >> 4) * 8 + (lane & 3) * 2 + ((lane >> 2) & 1),
                                 nzw(pack_bf(h0, h1)));
                }
                if (w == 2 && rbk == 0) {
                    uint4* pz = (uint4*)(out + ((lane >> 1) & 1) * DM + cbk * 16) + (lane & 1);
                    if (lane < 4) st_pub(pz, make_uint4(0, 0, 0, 0));
                    if (lane < 4 && confirm_store(pz) != 0) __trap();
                    __syncwarp();
                    if (lane < 6) st_pub(g_r + ((lane >> 1) * 28 + cbk) * 2 + (lane & 1), make_uint4(1, 1, 1, 1));
                }
            }
        }
        {
            constexpr float SC = 0.0625f * 1.4426950408889634f;
            float2* st = (float2*)(smem + SM_ST);
            float m0 = -INFINITY, m1 = -INFINITY, l0 = 0.f, l1 = 0.f;
#pragma unroll 1
            for (int h = 0; h < 2; h++) {
                if (h == 1 && w == 0 && proj) {
                    mbar_wait(bars + T_V * 8);
                    uint4* flag = g_r + ((rbk - 1) * 28 + cbk) * 2;
                    const uint32_t* pr = lane < 16 || rbk == 0 ? g_q + (b * 8 + (g ^ 1)) * 256 + (lane & 15) * 16
                                                               : (const uint32_t*)(flag + (lane & 1));
                    uint32_t n = 0;
#pragma unroll 1
                    while (!__all_sync(0xffffffffu, ld_poll32(pr) != 0)) {
                        if (++n > SPIN_LIMIT) __trap();
                        __nanosleep(300);
                    }
                    if (rbk != 0 && lane < 2) st_pub(flag + lane, make_uint4(0, 0, 0, 0));
                }
                mbar_wait(bars + (BAR_EMPTY + (h ? T_V + 2 : 14)) * 8);
                const uint4* ps = g_mb + ((c & ~7) + w) * MB_SIZE + MB_S + h * 64 + (lane >> 1) * 4 + (lane & 1);
                uint4 A, B;
                gather2(A, B, ps, ps + 2, 200);
                const uint32_t wa[4] = {A.x, A.y, A.z, A.w}, wb[4] = {B.x, B.y, B.z, B.w};
                float n0 = m0, n1 = m1;
#pragma unroll
                for (int k = 0; k < 4; k++) {
                    n0 = fmaxf(n0, fmaxf(bf_lo(wa[k]), bf_lo(wb[k])));
                    n1 = fmaxf(n1, fmaxf(bf_hi(wa[k]), bf_hi(wb[k])));
                }
#pragma unroll
                for (int m = 16; m; m >>= 1) { n0 = fmaxf(n0, shx(n0, m)); n1 = fmaxf(n1, shx(n1, m)); }
                if (lane == 0) st[h * 8 + w] = make_float2(n0, n1);
                bar_sync(NB_E, 256);
#pragma unroll
                for (int k = 0; k < 8; k++) { const float2 v = st[h * 8 + k]; n0 = fmaxf(n0, v.x); n1 = fmaxf(n1, v.y); }
                const float f0 = ex2((m0 - n0) * SC), f1 = ex2((m1 - n1) * SC);
                m0 = n0; m1 = n1;
                l0 *= f0; l1 *= f1;
                uint32_t* pp = (uint32_t*)(smem + SM_P) + (h * 8 + (lane & 1) * 4) * 256 + (w >> 1) * 64 + ((lane >> 1) & 3) * 8 +
                               (w & 1) * 4 + (lane >> 3);
#pragma unroll
                for (int k = 0; k < 4; k++) {
                    const float a0 = ex2((bf_lo(wa[k]) - m0) * SC), b0 = ex2((bf_lo(wb[k]) - m0) * SC);
                    const float a1 = ex2((bf_hi(wa[k]) - m1) * SC), b1 = ex2((bf_hi(wb[k]) - m1) * SC);
                    l0 += a0 + b0; l1 += a1 + b1;
                    pp[k * 256] = pack_bf(a0, b0);
                    pp[k * 256 + 32] = pack_bf(a1, b1);
                }
                if (h == 1) {
#pragma unroll
                    for (int m = 16; m; m >>= 1) { l0 += shx(l0, m); l1 += shx(l1, m); }
                    if (lane == 0) st[16 + w] = make_float2(l0, l1);
                    if (tid == 0) st[24] = make_float2(f0, f1);
                }
                __syncwarp();
                bar_arrive(NB_P0 + h, 384);
            }
        }
        if (proj) {
            uint32_t wa = sb + SM_RING + (w * 32 + (lane & 7) + 8 * (lane >> 4)) * 32 + 16 * (((lane >> 3) ^ (lane >> 2)) & 1);
            uint32_t wbar = bars + T_WD * 8, odd = t & 1;
            uint32_t rs = sb + SM_RED + 2048 + (w * 32 + 8 * t + g8) * 4, rl = sb + SM_RED + 2048 + (lane & 15) * 8;
            const uint4* src = g_mb + (rbk * 32 + w) * MB_SIZE;
            const uint4* po = src + (g8 >> 2) * 8 * MB_SIZE + MB_O + t;
            const int oidx = ((lane >> 3) & 1) * (DM / 2) + cbk * 8 + (lane & 7);
            uint32_t xw = rbk == 0 ? ((const uint32_t*)(smem + SM_X))[oidx] : 0;
            uint32_t* pout = lane < 16 ? (uint32_t*)out + oidx : nullptr;
            uint4* prs = s < 2 ? (uint4*)g_q + (b * 8 + g) * 64 + s * 32 + lane : nullptr;
            pin2(prs); pin2(wa); pin(wbar); pin2(odd); pin2(rs); pin2(rl); pin2(po); pin(xw); pin2(pout);
            float acc[4][4];
#pragma unroll
            for (int u = 0; u < 4; u++) acc[u][0] = acc[u][1] = acc[u][2] = acc[u][3] = 0.f;
            uint32_t n = 0;
            if (w < 7) {
                const uint2* ph = (const uint2*)(src + MB_H) + (g8 >> 2) * 4 + t;
                uint2 H[4];
#pragma unroll 1
                while (true) {
#pragma unroll
                    for (int k = 0; k < 4; k++) H[k] = ld_poll64(ph + k * 16 * MB_SIZE);
                    const uint32_t z = min(min(min(H[0].x, H[0].y), min(H[1].x, H[1].y)), min(min(H[2].x, H[2].y), min(H[3].x, H[3].y)));
                    if (__all_sync(0xffffffffu, z != 0)) break;
                    if (++n > SPIN_LIMIT) __trap();
                    __nanosleep(100);
                }
#pragma unroll
                for (int k = 0; k < 2; k++) {
                    const uint32_t off = ((T_WD + k) % RING) * TILE_BYTES;
                    mbar_wait(wbar + k * 8);
                    const uint4 Y0 = ldsm_t(wa + off), Y1 = ldsm_t(wa + off + 512);
                    mma(acc[2 * k], Y0, H[2 * k].x, H[2 * k].y);
                    mma(acc[2 * k + 1], Y1, H[2 * k + 1].x, H[2 * k + 1].y);
                }
            }
            uint4 O[4], Y[8];
            auto poll_o = [&]() {
                O[0] = ld_poll(po); O[1] = ld_poll(po + 4);
                O[2] = ld_poll(po + 16 * MB_SIZE); O[3] = ld_poll(po + 16 * MB_SIZE + 4);
            };
            auto load_w = [&](int k) {
                mbar_wait(wbar + (2 + k) * 8);
                Y[2 * k] = ldsm_t(wa + ((T_WO + k) % RING) * TILE_BYTES);
                Y[2 * k + 1] = ldsm_t(wa + ((T_WO + k) % RING) * TILE_BYTES + 512);
            };
            auto fold = [&]() { return odd ? (acc[0][2] + acc[1][2]) + (acc[2][2] + acc[3][2]) : (acc[0][0] + acc[1][0]) + (acc[2][0] + acc[3][0]); };
            load_w(0);
            load_w(1);
            poll_o();
            load_w(2);
            float ffn_part = fold();
            pin(ffn_part);
            n = 0;
            bool ok;
#pragma unroll 1
            do {
                if (++n > SPIN_LIMIT) __trap();
                load_w(3);
                ok = __all_sync(0xffffffffu, min(min(min4(O[0]), min4(O[1])), min(min4(O[2]), min4(O[3]))) != 0);
#pragma unroll
                for (int u = 0; u < 4; u++) acc[u][0] = acc[u][1] = acc[u][2] = acc[u][3] = 0.f;
                acc[0][0] = acc[0][2] = ffn_part;
#pragma unroll
                for (int k = 0; k < 4; k++) {
                    mma(acc[(2 * k) & 3], Y[2 * k], O[k].x, O[k].y);
                    mma(acc[(2 * k + 1) & 3], Y[2 * k + 1], O[k].z, O[k].w);
                }
                sts32f(rs, fold());
                if (!ok) poll_o();
            } while (!ok);
            bar_sync(NB_E, 256);
            if (w == 0) {
                float2 v[8];
#pragma unroll
                for (int k = 0; k < 8; k++) v[k] = lds64f(rl + k * 128);
                const float r0 = (((v[0].x + bf_lo(xw)) + v[1].x) + (v[2].x + v[3].x)) + ((v[4].x + v[5].x) + (v[6].x + v[7].x));
                const float r1 = (((v[0].y + bf_hi(xw)) + v[1].y) + (v[2].y + v[3].y)) + ((v[4].y + v[5].y) + (v[6].y + v[7].y));
                asm volatile("{ .reg .pred p; setp.ne.u64 p, %0, 0; @p red.relaxed.gpu.global.add.noftz.bf16x2 [%0], %1; }"
                             ::"l"(pout), "r"(pack_bf(r0, r1)) : "memory");
                if (prs) st_pub(prs, make_uint4(0, 0, 0, 0));
            }
        }
    }
}

typedef CUresult (*EncodeFn)(CUtensorMap*, CUtensorMapDataType, cuuint32_t, void*, const cuuint64_t*, const cuuint64_t*,
                             const cuuint32_t*, const cuuint32_t*, CUtensorMapInterleave, CUtensorMapSwizzle,
                             CUtensorMapL2promotion, CUtensorMapFloatOOBfill);

void make_map(EncodeFn fn, CUtensorMap* m, void* ptr, int rows, int cols, int box_rows, int box_cols) {
    const cuuint64_t dims[2] = {(cuuint64_t)cols, (cuuint64_t)rows}, strides[1] = {(cuuint64_t)cols * 2};
    const cuuint32_t box[2] = {(cuuint32_t)box_cols, (cuuint32_t)box_rows}, es[2] = {1, 1};
    fn(m, CU_TENSOR_MAP_DATA_TYPE_BFLOAT16, 2, ptr, dims, strides, box, es, CU_TENSOR_MAP_INTERLEAVE_NONE,
       box_cols == 32 ? CU_TENSOR_MAP_SWIZZLE_64B : CU_TENSOR_MAP_SWIZZLE_32B, CU_TENSOR_MAP_L2_PROMOTION_L2_128B,
       CU_TENSOR_MAP_FLOAT_OOB_FILL_NONE);
}

}

extern "C" void kernel_launch(void* const* d_in, const int* in_sizes, int n_in, void* d_out, int out_size) {
    (void)in_sizes; (void)n_in; (void)out_size;
    static EncodeFn encode = nullptr;
    if (!encode) {
        void* fn = nullptr;
        cudaDriverEntryPointQueryResult qr;
        cudaGetDriverEntryPoint("cuTensorMapEncodeTiled", &fn, cudaEnableDefault, &qr);
        encode = (EncodeFn)fn;
        cudaFuncSetAttribute(fused_decode_kernel, cudaFuncAttributeMaxDynamicSharedMemorySize, SM_TOTAL);
    }
    Maps maps;
    make_map(encode, &maps.v, d_in[2], 16 * SK, DH, 256, 32);
    make_map(encode, &maps.wq, d_in[3], DM, QD, 224, 32);
    make_map(encode, &maps.wg, d_in[6], DM, FF, 224, 16);
    make_map(encode, &maps.wu, d_in[7], DM, FF, 224, 16);
    make_map(encode, &maps.wo, d_in[4], QD, DM, 256, 16);
    make_map(encode, &maps.wd, d_in[8], FF, DM, 224, 16);
    fused_decode_kernel<<<NCTA, NTHREADS, SM_TOTAL>>>((const __nv_bfloat16*)d_in[0], (const __nv_bfloat16*)d_in[1],
                                                      (__nv_bfloat16*)d_out, maps);
}
```

```cpp
#include <cuda_runtime.h>
#include <cuda.h>
#include <cuda_bf16.h>
#include <stdint.h>

namespace {

constexpr int DM = 448, FF = 1792, SK = 32768, WIN = 4096, DH = 256, QD = 4096;
constexpr int NCTA = 128, NTHREADS = 13 * 32;
constexpr uint32_t SPIN_LIMIT = 1u << 20;

constexpr int TILE_BYTES = 16384, NT = 16, RING = 12;
constexpr int T_K0 = 2, T_F0 = 8, T_F1 = 11, T_V = 4 + NT, T_WD = T_V + NT, T_WO = T_WD + 2, NTILE = T_WO + 4;
constexpr int HALF_BYTES = 224 * 64, WD_BYTES = 224 * 32, WO_BYTES = 256 * 32;
constexpr int W1 = 3, WMIN = 2, WMAX = 4, WMAX_FROM = 10;
constexpr uint32_t T0 = 1370, TAU_K = 617, TAU_V = 638, TAU_W = 290, T_SHIFT = 400;
constexpr int STAGGER = 24;

constexpr int SM_RING = 0;
constexpr int SM_P = SM_RING + RING * TILE_BYTES;
constexpr int SM_QS = SM_P + 16384;
constexpr int SM_X = SM_QS + 1024;
constexpr int SM_XN = SM_X + 1792;
constexpr int SM_RED = SM_XN + 1792;
constexpr int SM_ST = SM_RED + 4096;
constexpr int SM_BAR = SM_ST + 256;
constexpr int BAR_EMPTY = NTILE, NEMPTY = NTILE - RING, NBAR = NTILE + NEMPTY, BAR_X = NBAR;
constexpr int SM_TOTAL = SM_BAR + (NBAR + 2) * 8;
static_assert(NEMPTY > T_V + 2 && NEMPTY <= T_WD && T_F1 < RING && SM_TOTAL <= 232448, "layout");

constexpr int MB_S = 0, MB_O = 128, MB_H = 136, MB_PAD = 140, MB_SIZE = 144;
__device__ __align__(128) uint32_t g_q[16 * 256];
__device__ __align__(128) uint4 g_r[84 * 2];
__device__ __align__(128) uint4 g_mb[NCTA * MB_SIZE];

__device__ __forceinline__ void mbar_init(uint32_t bar, uint32_t cnt) {
    asm volatile("mbarrier.init.shared::cta.b64 [%0], %1;" ::"r"(bar), "r"(cnt) : "memory");
}
__device__ __forceinline__ void mbar_expect(uint32_t bar, uint32_t bytes) {
    asm volatile("mbarrier.arrive.expect_tx.shared::cta.b64 _, [%0], %1;" ::"r"(bar), "r"(bytes) : "memory");
}
__device__ __forceinline__ void mbar_arrive(uint32_t bar) {
    asm volatile("mbarrier.arrive.shared::cta.b64 _, [%0];" ::"r"(bar) : "memory");
}
__device__ __forceinline__ void mbar_wait(uint32_t bar) {
    uint32_t done, n = 0;
#pragma unroll 1
    do {
        if (++n > SPIN_LIMIT) __trap();
        asm volatile("{\n.reg .pred p;\nmbarrier.try_wait.parity.shared::cta.b64 p, [%1], 0;\nselp.u32 %0, 1, 0, p;\n}"
                     : "=r"(done) : "r"(bar) : "memory");
    } while (!done);
}
__device__ __forceinline__ bool mbar_test(uint32_t bar) {
    uint32_t done;
    asm volatile("{\n.reg .pred p;\nmbarrier.test_wait.parity.shared::cta.b64 p, [%1], 0;\nselp.u32 %0, 1, 0, p;\n}"
                 : "=r"(done) : "r"(bar) : "memory");
    return done;
}
__device__ __forceinline__ uint32_t now_ns() {
    uint32_t t;
    asm volatile("mov.u32 %0, %%globaltimer_lo;" : "=r"(t));
    return t;
}
__device__ __forceinline__ void mbar_wait_until(uint32_t bar, uint32_t deadline) {
#pragma unroll 1
    for (uint32_t n = 0; n < SPIN_LIMIT; n++) {
        const int32_t left = (int32_t)(deadline - now_ns());
        if (left <= 0) break;
        if (left > 100) {
            if (mbar_test(bar)) break;
            __nanosleep(20);
        }
    }
}
__device__ __forceinline__ void bulk_load(uint32_t dst, const void* src, uint32_t bytes, uint32_t bar, uint64_t pol) {
    asm volatile("cp.async.bulk.shared::cluster.global.mbarrier::complete_tx::bytes.L2::cache_hint [%0], [%1], %2, [%3], %4;"
                 ::"r"(dst), "l"(src), "r"(bytes), "r"(bar), "l"(pol) : "memory");
}
__device__ __forceinline__ void tensor_load(uint32_t dst, const CUtensorMap* map, int col, int row, uint32_t bar, uint64_t pol) {
    asm volatile("cp.async.bulk.tensor.2d.shared::cluster.global.mbarrier::complete_tx::bytes.L2::cache_hint [%0], [%1, {%2, %3}], [%4], %5;"
                 ::"r"(dst), "l"(map), "r"(col), "r"(row), "r"(bar), "l"(pol) : "memory");
}
__device__ __forceinline__ void pin(uint32_t& v) { asm volatile("" : "+r"(v)); }
__device__ __forceinline__ void pin(float& v) { asm volatile("" : "+f"(v)); }
__device__ __forceinline__ void pin2(uint32_t& v) { v = __shfl_xor_sync(0xffffffffu, v, 0); }
template <class T> __device__ __forceinline__ void pin2(T*& p) { p = (T*)__shfl_xor_sync(0xffffffffu, (unsigned long long)p, 0); }
__device__ __forceinline__ void bar_sync(int id, int n) { asm volatile("bar.sync %0, %1;" ::"r"(id), "r"(n) : "memory"); }
__device__ __forceinline__ void bar_arrive(int id, int n) { asm volatile("bar.arrive %0, %1;" ::"r"(id), "r"(n) : "memory"); }
__device__ __forceinline__ uint4 lds128(uint32_t a) {
    uint4 v;
    asm volatile("ld.shared.v4.u32 {%0,%1,%2,%3}, [%4];" : "=r"(v.x), "=r"(v.y), "=r"(v.z), "=r"(v.w) : "r"(a) : "memory");
    return v;
}
__device__ __forceinline__ float2 lds64f(uint32_t a) {
    float2 v;
    asm volatile("ld.shared.v2.f32 {%0,%1}, [%2];" : "=f"(v.x), "=f"(v.y) : "r"(a) : "memory");
    return v;
}
__device__ __forceinline__ void sts32f(uint32_t a, float v) { asm volatile("st.shared.f32 [%0], %1;" ::"r"(a), "f"(v) : "memory"); }
__device__ __forceinline__ uint4 ldsm_t(uint32_t a) {
    uint4 v;
    asm volatile("ldmatrix.sync.aligned.m8n8.x4.trans.shared.b16 {%0,%1,%2,%3}, [%4];"
                 : "=r"(v.x), "=r"(v.y), "=r"(v.z), "=r"(v.w) : "r"(a) : "memory");
    return v;
}
__device__ __forceinline__ uint4 ld_poll(const uint4* p) {
    uint4 v;
    asm volatile("ld.relaxed.gpu.global.v4.u32 {%0,%1,%2,%3}, [%4];" : "=r"(v.x), "=r"(v.y), "=r"(v.z), "=r"(v.w) : "l"(p) : "memory");
    return v;
}
__device__ __forceinline__ uint2 ld_poll64(const uint2* p) {
    uint2 v;
    asm volatile("ld.relaxed.gpu.global.v2.u32 {%0,%1}, [%2];" : "=r"(v.x), "=r"(v.y) : "l"(p) : "memory");
    return v;
}
__device__ __forceinline__ uint32_t ld_poll32(const uint32_t* p) {
    uint32_t v;
    asm volatile("ld.relaxed.gpu.global.u32 %0, [%1];" : "=r"(v) : "l"(p) : "memory");
    return v;
}
__device__ __forceinline__ void st_pub(uint4* p, uint4 v) {
    asm volatile("st.relaxed.gpu.global.v4.u32 [%0], {%1,%2,%3,%4};" ::"l"(p), "r"(v.x), "r"(v.y), "r"(v.z), "r"(v.w) : "memory");
}
__device__ __forceinline__ void st_pub64(void* p, uint32_t a, uint32_t b) {
    asm volatile("st.relaxed.gpu.global.v2.u32 [%0], {%1,%2};" ::"l"(p), "r"(a), "r"(b) : "memory");
}
__device__ __forceinline__ void st_pub32(uint32_t* p, uint32_t v) {
    asm volatile("st.relaxed.gpu.global.u32 [%0], %1;" ::"l"(p), "r"(v) : "memory");
}
__device__ __forceinline__ uint32_t confirm_store(const void* p) {
    uint32_t v;
    asm volatile("atom.relaxed.gpu.global.exch.b32 %0, [%1], 0;" : "=r"(v) : "l"(p) : "memory");
    return v;
}
__device__ __forceinline__ uint32_t min4(const uint4& v) { return min(min(v.x, v.y), min(v.z, v.w)); }
__device__ __forceinline__ uint32_t nzw(uint32_t w) { return w == 0 ? 0x8000u : w; }
__device__ __forceinline__ void mma(float (&c)[4], const uint4& a, uint32_t b0, uint32_t b1) {
    asm volatile("mma.sync.aligned.m16n8k16.row.col.f32.bf16.bf16.f32 {%0,%1,%2,%3}, {%4,%5,%6,%7}, {%8,%9}, {%0,%1,%2,%3};"
                 : "+f"(c[0]), "+f"(c[1]), "+f"(c[2]), "+f"(c[3]) : "r"(a.x), "r"(a.y), "r"(a.z), "r"(a.w), "r"(b0), "r"(b1));
}
__device__ __forceinline__ float bf_lo(uint32_t w) { return __uint_as_float(w << 16); }
__device__ __forceinline__ float bf_hi(uint32_t w) { return __uint_as_float(w & 0xffff0000u); }
__device__ __forceinline__ float rbf(float f) { return __bfloat162float(__float2bfloat16_rn(f)); }
__device__ __forceinline__ uint32_t pack_bf(float lo, float hi) {
    uint32_t r;
    asm("cvt.rn.bf16x2.f32 %0, %1, %2;" : "=r"(r) : "f"(hi), "f"(lo));
    return r;
}
__device__ __forceinline__ float ex2(float v) {
    float r;
    asm("ex2.approx.ftz.f32 %0, %1;" : "=f"(r) : "f"(v));
    return r;
}
__device__ __forceinline__ float asf(uint32_t u) { return __uint_as_float(u); }
__device__ __forceinline__ float shx(float v, int m) { return __shfl_xor_sync(0xffffffffu, v, m); }

__device__ __forceinline__ void gemv0(uint32_t waddr, int step, uint32_t xaddr, int g8, int t, float* red) {
    const uint32_t lo = (g8 & 1) ? 0x1044u : 0x4410u, hi = (g8 & 1) ? 0x3244u : 0x4432u;
    const uint32_t s0 = (g8 & 2) ? 0x4444u : lo, s1 = (g8 & 2) ? 0x4444u : hi;
    const uint32_t s2 = (g8 & 2) ? lo : 0x4444u, s3 = (g8 & 2) ? hi : 0x4444u;
    float c0[4] = {0.f, 0.f, 0.f, 0.f}, c1[4] = {0.f, 0.f, 0.f, 0.f};
#pragma unroll
    for (int i = 0; i < 7; i++) {
        const uint4 X = lds128(waddr + i * step);
        uint32_t xw;
        asm volatile("ld.shared.u32 %0, [%1];" : "=r"(xw) : "r"(xaddr + i * 16) : "memory");
        const uint4 a = make_uint4(__byte_perm(xw, 0, s0), __byte_perm(xw, 0, s1), __byte_perm(xw, 0, s2), __byte_perm(xw, 0, s3));
        mma(c0, a, X.x, X.y);
        mma(c1, a, X.z, X.w);
    }
    red[(g8 >> 2) * 32 + 8 * t + (g8 & 3)] = c0[0] + c0[3];
    red[(g8 >> 2) * 32 + 8 * t + (g8 & 3) + 4] = c1[0] + c1[3];
}

__device__ __forceinline__ void gather2(uint4& v0, uint4& v1, const uint4* p0, const uint4* p1, unsigned sleep_ns) {
    uint32_t n = 0;
#pragma unroll 1
    while (true) {
        v0 = ld_poll(p0);
        v1 = ld_poll(p1);
        if (__all_sync(0xffffffffu, min(min4(v0), min4(v1)) != 0)) break;
        if (++n > SPIN_LIMIT) __trap();
        __nanosleep(sleep_ns);
    }
}

enum { NB_R = 1, NB_A = 2, NB_E = 3, NB_X = 4, NB_P0 = 5, NB_P1 = 6, NB_F = 7 };

struct Maps { CUtensorMap v, wq, wg, wu, wo, wd; };

__global__ void __launch_bounds__(NTHREADS, 1)
fused_decode_kernel(const __nv_bfloat16* __restrict__ x, const __nv_bfloat16* __restrict__ kc,
                    __nv_bfloat16* __restrict__ out, const __grid_constant__ Maps maps) {
    extern __shared__ __align__(1024) unsigned char smem[];
    const uint32_t sb = (uint32_t)__cvta_generic_to_shared(smem);
    const int c = blockIdx.x, g = c >> 4, j = c & 15, b = j >> 3, s = j & 7;
    const uint32_t bars = sb + SM_BAR;
    const int row0 = (b * 8 + g) * SK + (SK - WIN);
    {
        const uint32_t off = (uint32_t)(row0 + s * 32) * (DH * 2) + (TILE_BYTES - 128) - threadIdx.x * 128;
        asm volatile("{ .reg .pred p; .reg .u64 a; cvt.u64.u32 a, %1; add.u64 a, a, %0; setp.lt.u32 p, %2, 128; @p prefetch.global.L2 [a]; }"
                     ::"l"(kc), "r"(off), "r"(threadIdx.x) : "memory");
    }
    const int warp = __shfl_sync(0xffffffffu, threadIdx.x >> 5, 0), lane = threadIdx.x & 31;
    const bool proj = s < 7;
    const int cbk = (g & 1) * 14 + 2 * s + b, rbk = g >> 1;

    if (warp == 0) {
        const char* kp = (const char*)kc + (size_t)(row0 + s * 32) * (DH * 2);
        uint64_t pol;
        asm volatile("createpolicy.fractional.L2::evict_first.b64 %0, 1.0;" : "=l"(pol));
        if (lane == 0) {
            *(volatile uint32_t*)(smem + SM_ST + 240) = now_ns();
            mbar_init(bars + T_K0 * 8, 1);
            mbar_expect(bars + T_K0 * 8, TILE_BYTES);
            bulk_load(sb + SM_RING + T_K0 * TILE_BYTES, kp, TILE_BYTES, bars + T_K0 * 8, pol);
#pragma unroll
            for (int i = 0; i < 2; i++) {
                mbar_init(bars + i * 8, 1);
                mbar_expect(bars + i * 8, HALF_BYTES);
                tensor_load(sb + SM_RING + i * TILE_BYTES, &maps.wq, c * 32, i * 224, bars + i * 8, pol);
            }
        }
        __syncwarp();
        bar_sync(0, NTHREADS);
        if (lane == 0) {
            uint32_t dst = sb + SM_RING + W1 * TILE_BYTES, bar = bars + W1 * 8;
            const int stag = (2 * g - 7) * STAGGER;
            uint32_t deadline = *(volatile uint32_t*)(smem + SM_ST + 240) + T0 + stag;
            auto ready = [&](int i, uint32_t bytes) {
                if (i >= RING) mbar_wait(bar + (BAR_EMPTY - RING) * 8);
                if (i >= WMAX_FROM && i < T_WD && !mbar_test(bar - WMAX * 8)) {
                    mbar_wait(bar - WMAX * 8);
                    const uint32_t t = now_ns() + T_SHIFT;
                    if ((int32_t)(t - deadline) > 0) deadline = t;
                }
                mbar_expect(bar, bytes);
                mbar_wait_until(bar - WMIN * 8, deadline);
            };
            auto next = [&](uint32_t tau) {
                deadline += tau;
                bar += 8;
                dst += TILE_BYTES;
                if (dst == sb + SM_RING + RING * TILE_BYTES) dst = sb + SM_RING;
            };
#pragma unroll 1
            for (int i = W1; i < T_V; i++) {
                if (i == T_F0 || i == T_F1) {
                    ready(i, proj ? HALF_BYTES : 0);
                    if (proj) {
                        tensor_load(dst, &maps.wg, (rbk * 28 + cbk) * 16, i == T_F0 ? 0 : 224, bar, pol);
                        tensor_load(dst + HALF_BYTES / 2, &maps.wu, (rbk * 28 + cbk) * 16, i == T_F0 ? 0 : 224, bar, pol);
                    }
                    if (i == T_F1) {
                        asm volatile("prefetch.tensormap [%0];" ::"l"(&maps.v) : "memory");
                        asm volatile("prefetch.tensormap [%0];" ::"l"(&maps.wd) : "memory");
                        asm volatile("prefetch.tensormap [%0];" ::"l"(&maps.wo) : "memory");
                    }
                } else {
                    kp += 8 * TILE_BYTES;
                    ready(i, TILE_BYTES);
                    bulk_load(dst, kp, TILE_BYTES, bar, pol);
                }
                next(TAU_K);
            }
#pragma unroll 1
            for (int i = T_V; i < T_WD; i++) {
                ready(i, TILE_BYTES);
                tensor_load(dst, &maps.v, s * 32, row0 + (i - T_V) * 256, bar, pol);
                next(TAU_V);
                if (i == T_WD - 3 || i == T_WD - 2) deadline -= stag / 2;
            }
            if (proj) {
#pragma unroll 1
                for (int i = T_WD; i < NTILE; i++) {
                    const bool wd = i < T_WO;
                    ready(i, wd ? WD_BYTES : WO_BYTES);
                    tensor_load(dst, wd ? &maps.wd : &maps.wo, cbk * 16,
                                wd ? rbk * 448 + (i - T_WD) * 224 : rbk * 1024 + (i - T_WO) * 256, bar, pol);
                    next(TAU_W);
                }
            }
        }
    } else if (warp < 5) {
        const int w = warp - 1;
        const int g8 = lane >> 2, t = lane & 3;
        if (w < 2) {
            if (lane == 0) {
                mbar_init(bars + (BAR_X + w) * 8, 1);
                mbar_expect(bars + (BAR_X + w) * 8, DM * 2);
                asm volatile("cp.async.bulk.shared::cluster.global.mbarrier::complete_tx::bytes [%0], [%1], %2, [%3];"
                             ::"r"(sb + SM_X + w * DM * 2), "l"(x + w * DM), "r"(DM * 2), "r"(bars + (BAR_X + w) * 8) : "memory");
            }
            __syncwarp();
            bar_arrive(0, NTHREADS);
            mbar_wait(bars + (BAR_X + w) * 8);
            uint32_t xw[7];
#pragma unroll
            for (int i = 0; i < 7; i++) xw[i] = ((const uint32_t*)(smem + SM_X))[w * (DM / 2) + lane + 32 * i];
            float sum = 0.f;
#pragma unroll
            for (int i = 0; i < 7; i++) sum += bf_lo(xw[i]) + bf_hi(xw[i]);
#pragma unroll
            for (int m = 16; m; m >>= 1) sum += shx(sum, m);
            const float mu = sum * (1.f / DM);
            float q = 0.f;
#pragma unroll
            for (int i = 0; i < 7; i++) {
                const float d0 = bf_lo(xw[i]) - mu, d1 = bf_hi(xw[i]) - mu;
                q = fmaf(d0, d0, fmaf(d1, d1, q));
            }
#pragma unroll
            for (int m = 16; m; m >>= 1) q += shx(q, m);
            const float mean = rbf(mu);
            const float inv = 1.f / rbf(sqrtf(rbf(rbf(q * (1.f / DM)) + 1e-5f)));
#pragma unroll
            for (int i = 0; i < 7; i++)
                ((uint32_t*)(smem + SM_XN))[w * (DM / 2) + lane + 32 * i] =
                    pack_bf(rbf(bf_lo(xw[i]) - mean) * inv, rbf(bf_hi(xw[i]) - mean) * inv);
            bar_arrive(NB_X, 320);
        } else if (w == 2) {
            bar_sync(0, NTHREADS);
            const uint4* pq = (const uint4*)g_q + (b * 8 + g) * 64 + lane;
            uint4 v0, v1;
            gather2(v0, v1, pq, pq + 32, 50);
            ((uint4*)(smem + SM_QS))[lane] = v0;
            ((uint4*)(smem + SM_QS))[lane + 32] = v1;
        } else {
            bar_sync(0, NTHREADS);
            bar_sync(NB_R, 288);
            const float2* red = (const float2*)(smem + SM_RED);
            float2 a = red[lane];
#pragma unroll
            for (int k = 1; k < 8; k++) { const float2 v = red[k * 32 + lane]; a.x += v.x; a.y += v.y; }
            st_pub32(g_q + ((lane >> 4) * 8 + g) * 256 + j * 16 + (lane & 15), nzw(pack_bf(a.x, a.y)));
        }
        __syncwarp();
        bar_sync(NB_A, 128);
        int slot = T_K0;
        {
            uint32_t qf[8][2];
#pragma unroll
            for (int k = 0; k < 8; k++) {
                const uint32_t* qw = (const uint32_t*)(smem + SM_QS) + (g8 & 1) * 128 +
                                     ((k >> 1) * 8 + t + 4 * ((k & 1) ^ (g8 >> 2))) * 4 + ((g8 >> 1) & 1);
                qf[k][0] = qw[0];
                qf[k][1] = qw[2];
            }
            uint32_t ko0 = sb + SM_RING + (w * 8 + g8) * 512 + 16 * (t + 4 * (g8 & 1));
            uint32_t ko1 = ko0 ^ 64;
            pin(ko0); pin(ko1);
            uint32_t keep0 = 0, keep1 = 0;
            int pos = T_K0;
#pragma unroll 1
            for (int i = 0; i < NT; i++) {
                const uint32_t b0 = ko0 + slot * TILE_BYTES, b1 = ko1 + slot * TILE_BYTES;
                mbar_wait(bars + pos * 8);
                uint4 X[8];
#pragma unroll
                for (int k = 0; k < 4; k++) { X[2 * k] = lds128(b0 + k * 128); X[2 * k + 1] = lds128(b1 + k * 128); }
                float c0[4] = {0.f, 0.f, 0.f, 0.f}, c1[4] = {0.f, 0.f, 0.f, 0.f};
#pragma unroll
                for (int k = 0; k < 4; k++) {
                    mma(c0, X[2 * k], qf[2 * k][0], qf[2 * k][1]);
                    mma(c1, X[2 * k + 1], qf[2 * k + 1][0], qf[2 * k + 1][1]);
                }
                __syncwarp();
                if (lane == 0) mbar_arrive(bars + (BAR_EMPTY + pos) * 8);
                float s0 = (t & 1) ? c0[2] + c1[2] : c0[0] + c1[0], s1 = (t & 1) ? c0[3] + c1[3] : c0[1] + c1[1];
                s0 += shx(s0, 1);
                s1 += shx(s1, 1);
                const uint32_t word = __shfl_sync(0xffffffffu, nzw(pack_bf(s0, s1)), (lane & ~3) + 2 * (g8 & 1));
                if (((i >> 1) & 3) == t) { if (i & 1) keep1 = word; else keep0 = word; }
                if ((i & 7) == 7) st_pub64((uint2*)(g_mb + c * MB_SIZE + MB_S) + (i >> 3) * 128 + w * 32 + lane, keep0, keep1);
                do { pos++; if (++slot == RING) slot = 0; } while (pos == T_F0 || pos == T_F1);
            }
        }
        float acc[4][4];
#pragma unroll
        for (int u = 0; u < 4; u++) acc[u][0] = acc[u][1] = acc[u][2] = acc[u][3] = 0.f;
        uint32_t vo = sb + SM_RING + w * 4096 + ((lane & 7) + 8 * (lane >> 4)) * 64 + 16 * (((lane >> 3) & 1) ^ ((lane >> 1) & 3));
        uint32_t po = sb + SM_P + ((w * 2 + (g8 >> 2)) * 4 + t) * 32;
        uint32_t ro = sb + SM_RED + (w * 64 + 16 * t + g8) * 4, rl = sb + SM_RED + lane * 8, odd = t & 1;
        uint32_t* dsto = (uint32_t*)(g_mb + c * MB_SIZE + MB_O) + (lane & 16) + (lane & 3) * 4 + ((lane >> 2) & 3);
        pin(vo); pin(po); pin2(ro); pin2(rl); pin2(odd); pin2(dsto);
        float inv_l = 0.f;
#pragma unroll 1
        for (int i = 0; i < NT; i++) {
            if (i == 0) bar_sync(NB_P0, 384);
            if (i == 8) {
                bar_sync(NB_P1, 384);
                const float f = ((const float*)(smem + SM_ST + 192))[t >> 1];
#pragma unroll
                for (int u = 0; u < 4; u++) { acc[u][0] *= f; acc[u][2] *= f; }
                float l = 0.f;
#pragma unroll
                for (int k = 0; k < 8; k++) l += ((const float*)(smem + SM_ST + 128))[2 * k + (lane >> 4)];
                inv_l = 1.f / l;
            }
            const uint4 P0 = lds128(po + i * 1024), P1 = lds128(po + i * 1024 + 16);
            uint32_t b0 = vo + slot * TILE_BYTES, b1 = b0 ^ 32;
            pin(b0); pin(b1);
            mbar_wait(bars + (T_V + i) * 8);
            uint4 X[8];
#pragma unroll
            for (int k = 0; k < 4; k++) { X[2 * k] = ldsm_t(b0 + k * 1024); X[2 * k + 1] = ldsm_t(b1 + k * 1024); }
            mma(acc[0], X[0], P0.x, P0.y); mma(acc[1], X[1], P0.x, P0.y);
            mma(acc[2], X[2], P0.z, P0.w); mma(acc[3], X[3], P0.z, P0.w);
            mma(acc[0], X[4], P1.x, P1.y); mma(acc[1], X[5], P1.x, P1.y);
            mma(acc[2], X[6], P1.z, P1.w); mma(acc[3], X[7], P1.z, P1.w);
            if (T_V + i < NEMPTY) {
                __syncwarp();
                if (lane == 0) mbar_arrive(bars + (BAR_EMPTY + T_V + i) * 8);
            }
            if (++slot == RING) slot = 0;
        }
        sts32f(ro, odd ? acc[1][0] + acc[3][0] : acc[0][0] + acc[2][0]);
        sts32f(ro + 32, odd ? acc[1][2] + acc[3][2] : acc[0][2] + acc[2][2]);
        if (w != 0) {
            bar_arrive(NB_A, 128);
        } else {
            bar_sync(NB_A, 128);
            const float2 v0 = lds64f(rl), v1 = lds64f(rl + 256), v2 = lds64f(rl + 512), v3 = lds64f(rl + 768);
            st_pub32(dsto, nzw(pack_bf(((v0.x + v1.x) + (v2.x + v3.x)) * inv_l, ((v0.y + v1.y) + (v2.y + v3.y)) * inv_l)));
        }
    } else {
        const int w = warp - 5, tid = threadIdx.x - 160;
        const int g8 = lane >> 2, t = lane & 3;
        {
            if (lane == 0) {
#pragma unroll
                for (int k = 0; k < (NBAR - W1 + 7) / 8; k++) {
                    const int i = W1 + w + 8 * k;
                    if (i < NBAR) mbar_init(bars + i * 8, i < BAR_EMPTY ? 1 : 4);
                }
                asm volatile("fence.mbarrier_init.release.cluster;" ::: "memory");
            }
            __syncwarp();
            bar_sync(0, NTHREADS);
            uint4* mb = g_mb + c * MB_SIZE + tid;
            if (tid < MB_SIZE) st_pub(mb, make_uint4(0, 0, 0, 0));
            const uint32_t back = tid < MB_SIZE && !(tid & 1) ? confirm_store(mb) : 0;
            bar_sync(NB_X, 320);
            const uint32_t xaddr = sb + SM_XN + (g8 >> 2) * (DM * 2) + (w * 28 + t) * 4;
            const int row = (w & 3) * 56 + 2 * t + (g8 & 1);
            float* redf = (float*)(smem + SM_RED);
            const float2* red = (const float2*)redf;
            const int tq = w >> 2, tf = w >> 2 ? T_F1 : T_F0;
            mbar_wait(bars + tq * 8);
            gemv0(sb + SM_RING + tq * TILE_BYTES + row * 64 + 16 * ((g8 >> 1) ^ t), 512, xaddr, g8, t, redf + w * 64);
            if (back != 0) __trap();
            __syncwarp();
            if (lane == 0) mbar_arrive(bars + (BAR_EMPTY + tq) * 8);
            bar_arrive(NB_R, 288);
            if (proj) {
                mbar_wait(bars + tf * 8);
                gemv0(sb + SM_RING + tf * TILE_BYTES + (g8 >> 2) * (HALF_BYTES / 2) + row * 32 + 16 * (((g8 >> 1) & 1) ^ (t >> 1)),
                      256, xaddr, g8, t, redf + 512 + w * 64);
            }
            __syncwarp();
            if (lane == 0) mbar_arrive(bars + (BAR_EMPTY + tf) * 8);
            if (proj) {
                bar_sync(NB_E, 256);
                if (w == 1) {
                    float2 a = red[256 + lane];
#pragma unroll
                    for (int k = 1; k < 8; k++) { const float2 v = red[256 + k * 32 + lane]; a.x += v.x; a.y += v.y; }
                    a.x = rbf(a.x); a.y = rbf(a.y);
                    const float u0 = shx(a.x, 8), u1 = shx(a.y, 8);
                    const float h0 = (a.x * (a.x > 0.f ? 1.f : 0.f)) * u0, h1 = (a.y * (a.y > 0.f ? 1.f : 0.f)) * u1;
                    if (!(lane & 8))
                        st_pub32((uint32_t*)(g_mb + c * MB_SIZE + MB_H) + (lane >> 4) * 8 + (lane & 3) * 2 + ((lane >> 2) & 1),
                                 nzw(pack_bf(h0, h1)));
                }
                if (w == 2 && rbk == 0) {
                    uint4* pz = (uint4*)(out + ((lane >> 1) & 1) * DM + cbk * 16) + (lane & 1);
                    if (lane < 4) st_pub(pz, make_uint4(0, 0, 0, 0));
                    if (lane < 4 && confirm_store(pz) != 0) __trap();
                    __syncwarp();
                    if (lane < 6) st_pub(g_r + ((lane >> 1) * 28 + cbk) * 2 + (lane & 1), make_uint4(1, 1, 1, 1));
                }
            }
        }
        {
            constexpr float SC = 0.0625f * 1.4426950408889634f;
            float2* st = (float2*)(smem + SM_ST);
            float m0 = -INFINITY, m1 = -INFINITY, l0 = 0.f, l1 = 0.f;
#pragma unroll 1
            for (int h = 0; h < 2; h++) {
                if (h == 1 && w == 0 && proj) {
                    mbar_wait(bars + T_V * 8);
                    uint4* flag = g_r + ((rbk - 1) * 28 + cbk) * 2;
                    const uint32_t* pr = lane < 16 || rbk == 0 ? g_q + (b * 8 + (g ^ 1)) * 256 + (lane & 15) * 16
                                                               : (const uint32_t*)(flag + (lane & 1));
                    uint32_t n = 0;
#pragma unroll 1
                    while (!__all_sync(0xffffffffu, ld_poll32(pr) != 0)) {
                        if (++n > SPIN_LIMIT) __trap();
                        __nanosleep(300);
                    }
                    if (rbk != 0 && lane < 2) st_pub(flag + lane, make_uint4(0, 0, 0, 0));
                }
                mbar_wait(bars + (BAR_EMPTY + (h ? T_V + 2 : 14)) * 8);
                const uint4* ps = g_mb + ((c & ~7) + w) * MB_SIZE + MB_S + h * 64 + (lane >> 1) * 4 + (lane & 1);
                uint4 A, B;
                gather2(A, B, ps, ps + 2, 200);
                const uint32_t wa[4] = {A.x, A.y, A.z, A.w}, wb[4] = {B.x, B.y, B.z, B.w};
                float n0 = m0, n1 = m1;
#pragma unroll
                for (int k = 0; k < 4; k++) {
                    n0 = fmaxf(n0, fmaxf(bf_lo(wa[k]), bf_lo(wb[k])));
                    n1 = fmaxf(n1, fmaxf(bf_hi(wa[k]), bf_hi(wb[k])));
                }
#pragma unroll
                for (int m = 16; m; m >>= 1) { n0 = fmaxf(n0, shx(n0, m)); n1 = fmaxf(n1, shx(n1, m)); }
                if (lane == 0) st[h * 8 + w] = make_float2(n0, n1);
                bar_sync(NB_E, 256);
#pragma unroll
                for (int k = 0; k < 8; k++) { const float2 v = st[h * 8 + k]; n0 = fmaxf(n0, v.x); n1 = fmaxf(n1, v.y); }
                const float f0 = ex2((m0 - n0) * SC), f1 = ex2((m1 - n1) * SC);
                m0 = n0; m1 = n1;
                l0 *= f0; l1 *= f1;
                uint32_t* pp = (uint32_t*)(smem + SM_P) + (h * 8 + (lane & 1) * 4) * 256 + (w >> 1) * 64 + ((lane >> 1) & 3) * 8 +
                               (w & 1) * 4 + (lane >> 3);
#pragma unroll
                for (int k = 0; k < 4; k++) {
                    const float a0 = ex2((bf_lo(wa[k]) - m0) * SC), b0 = ex2((bf_lo(wb[k]) - m0) * SC);
                    const float a1 = ex2((bf_hi(wa[k]) - m1) * SC), b1 = ex2((bf_hi(wb[k]) - m1) * SC);
                    l0 += a0 + b0; l1 += a1 + b1;
                    pp[k * 256] = pack_bf(a0, b0);
                    pp[k * 256 + 32] = pack_bf(a1, b1);
                }
                if (h == 1) {
#pragma unroll
                    for (int m = 16; m; m >>= 1) { l0 += shx(l0, m); l1 += shx(l1, m); }
                    if (lane == 0) st[16 + w] = make_float2(l0, l1);
                    if (tid == 0) st[24] = make_float2(f0, f1);
                }
                __syncwarp();
                bar_arrive(NB_P0 + h, 384);
            }
        }
        if (proj) {
            uint32_t wa = sb + SM_RING + (w * 32 + (lane & 7) + 8 * (lane >> 4)) * 32 + 16 * (((lane >> 3) ^ (lane >> 2)) & 1);
            uint32_t wbar = bars + T_WD * 8, odd = t & 1;
            uint32_t rs = sb + SM_RED + 2048 + (4 * t + (g8 >> 1)) * 80 + w * 8 + (g8 & 1) * 4, rl = sb + SM_RED + 2048 + (lane & 15) * 80;
            const uint4* src = g_mb + (rbk * 32 + w) * MB_SIZE;
            const uint4* po = src + (g8 >> 2) * 8 * MB_SIZE + MB_O + t;
            uint32_t* pout = (uint32_t*)out + ((lane >> 3) & 1) * (DM / 2) + cbk * 8 + (lane & 7);
            uint32_t* sink = (uint32_t*)(g_mb + c * MB_SIZE + MB_PAD) + (lane & 15);
            uint32_t fin = tid < 16;
            uint4* prs = s < 2 ? (uint4*)g_q + (b * 8 + g) * 64 + s * 32 + lane : nullptr;
            pin2(prs); pin2(wa); pin(wbar); pin2(odd); pin2(rs); pin2(rl); pin2(po); pin2(pout); pin2(sink); pin2(fin);
            float acc[4][4];
#pragma unroll
            for (int u = 0; u < 4; u++) acc[u][0] = acc[u][1] = acc[u][2] = acc[u][3] = 0.f;
            const float xres = rbk == 0 && w == 0 ? __bfloat162float(((const __nv_bfloat16*)(smem + SM_X))[(t >> 1) * DM + cbk * 16 + (t & 1) * 8 + g8]) : 0.f;
            uint32_t n = 0;
            if (w < 7) {
                const uint2* ph = (const uint2*)(src + MB_H) + (g8 >> 2) * 4 + t;
                uint2 H[4];
#pragma unroll 1
                while (true) {
#pragma unroll
                    for (int k = 0; k < 4; k++) H[k] = ld_poll64(ph + k * 16 * MB_SIZE);
                    const uint32_t z = min(min(min(H[0].x, H[0].y), min(H[1].x, H[1].y)), min(min(H[2].x, H[2].y), min(H[3].x, H[3].y)));
                    if (__all_sync(0xffffffffu, z != 0)) break;
                    if (++n > SPIN_LIMIT) __trap();
                    __nanosleep(100);
                }
#pragma unroll
                for (int k = 0; k < 2; k++) {
                    const uint32_t off = ((T_WD + k) % RING) * TILE_BYTES;
                    mbar_wait(wbar + k * 8);
                    const uint4 Y0 = ldsm_t(wa + off), Y1 = ldsm_t(wa + off + 512);
                    mma(acc[2 * k], Y0, H[2 * k].x, H[2 * k].y);
                    mma(acc[2 * k + 1], Y1, H[2 * k + 1].x, H[2 * k + 1].y);
                }
            }
            uint4 O[4], Y[8];
            auto poll_o = [&]() {
                O[0] = ld_poll(po); O[1] = ld_poll(po + 4);
                O[2] = ld_poll(po + 16 * MB_SIZE); O[3] = ld_poll(po + 16 * MB_SIZE + 4);
            };
            auto load_w = [&](int k) {
                mbar_wait(wbar + (2 + k) * 8);
                Y[2 * k] = ldsm_t(wa + ((T_WO + k) % RING) * TILE_BYTES);
                Y[2 * k + 1] = ldsm_t(wa + ((T_WO + k) % RING) * TILE_BYTES + 512);
            };
            auto fold = [&]() { return odd ? (acc[0][2] + acc[1][2]) + (acc[2][2] + acc[3][2]) : (acc[0][0] + acc[1][0]) + (acc[2][0] + acc[3][0]); };
            load_w(0);
            load_w(1);
            poll_o();
            load_w(2);
            float ffn_part = fold() + xres;
            pin(ffn_part);
            n = 0;
            uint32_t ok;
#pragma unroll 1
            do {
                if (++n > SPIN_LIMIT) __trap();
                load_w(3);
                const uint32_t z = min(min(min4(O[0]), min4(O[1])), min(min4(O[2]), min4(O[3])));
#pragma unroll
                for (int u = 0; u < 4; u++) acc[u][0] = acc[u][1] = acc[u][2] = acc[u][3] = 0.f;
                acc[0][0] = acc[0][2] = ffn_part;
#pragma unroll
                for (int k = 0; k < 4; k++) {
                    mma(acc[(2 * k) & 3], Y[2 * k], O[k].x, O[k].y);
                    mma(acc[(2 * k + 1) & 3], Y[2 * k + 1], O[k].z, O[k].w);
                }
                sts32f(rs, fold());
                asm volatile("{ .reg .pred p, q; setp.ne.u32 p, %1, 0; bar.red.and.pred q, %2, 256, p; selp.u32 %0, 1, 0, q; }"
                             : "=r"(ok) : "r"(z), "n"((int)NB_F) : "memory");
                if (fin) {
                    const uint4 v0 = lds128(rl), v1 = lds128(rl + 16), v2 = lds128(rl + 32), v3 = lds128(rl + 48);
                    const float r0 = ((asf(v0.x) + asf(v0.z)) + (asf(v1.x) + asf(v1.z))) + ((asf(v2.x) + asf(v2.z)) + (asf(v3.x) + asf(v3.z)));
                    const float r1 = ((asf(v0.y) + asf(v0.w)) + (asf(v1.y) + asf(v1.w))) + ((asf(v2.y) + asf(v2.w)) + (asf(v3.y) + asf(v3.w)));
                    asm volatile("red.relaxed.gpu.global.add.noftz.bf16x2 [%0], %1;" ::"l"(ok ? pout : sink), "r"(pack_bf(r0, r1)) : "memory");
                }
                if (ok && w != 1) return;
                if (!ok) { __syncwarp(); poll_o(); }
            } while (!ok);
            if (prs) st_pub(prs, make_uint4(0, 0, 0, 0));
        }
    }
}

typedef CUresult (*EncodeFn)(CUtensorMap*, CUtensorMapDataType, cuuint32_t, void*, const cuuint64_t*, const cuuint64_t*,
                             const cuuint32_t*, const cuuint32_t*, CUtensorMapInterleave, CUtensorMapSwizzle,
                             CUtensorMapL2promotion, CUtensorMapFloatOOBfill);

void make_map(EncodeFn fn, CUtensorMap* m, void* ptr, int rows, int cols, int box_rows, int box_cols) {
    const cuuint64_t dims[2] = {(cuuint64_t)cols, (cuuint64_t)rows}, strides[1] = {(cuuint64_t)cols * 2};
    const cuuint32_t box[2] = {(cuuint32_t)box_cols, (cuuint32_t)box_rows}, es[2] = {1, 1};
    fn(m, CU_TENSOR_MAP_DATA_TYPE_BFLOAT16, 2, ptr, dims, strides, box, es, CU_TENSOR_MAP_INTERLEAVE_NONE,
       box_cols == 32 ? CU_TENSOR_MAP_SWIZZLE_64B : CU_TENSOR_MAP_SWIZZLE_32B, CU_TENSOR_MAP_L2_PROMOTION_L2_128B,
       CU_TENSOR_MAP_FLOAT_OOB_FILL_NONE);
}

}

extern "C" void kernel_launch(void* const* d_in, const int* in_sizes, int n_in, void* d_out, int out_size) {
    (void)in_sizes; (void)n_in; (void)out_size;
    static EncodeFn encode = nullptr;
    if (!encode) {
        void* fn = nullptr;
        cudaDriverEntryPointQueryResult qr;
        cudaGetDriverEntryPoint("cuTensorMapEncodeTiled", &fn, cudaEnableDefault, &qr);
        encode = (EncodeFn)fn;
        cudaFuncSetAttribute(fused_decode_kernel, cudaFuncAttributeMaxDynamicSharedMemorySize, SM_TOTAL);
    }
    Maps maps;
    make_map(encode, &maps.v, d_in[2], 16 * SK, DH, 256, 32);
    make_map(encode, &maps.wq, d_in[3], DM, QD, 224, 32);
    make_map(encode, &maps.wg, d_in[6], DM, FF, 224, 16);
    make_map(encode, &maps.wu, d_in[7], DM, FF, 224, 16);
    make_map(encode, &maps.wo, d_in[4], QD, DM, 256, 16);
    make_map(encode, &maps.wd, d_in[8], FF, DM, 224, 16);
    fused_decode_kernel<<<NCTA, NTHREADS, SM_TOTAL>>>((const __nv_bfloat16*)d_in[0], (const __nv_bfloat16*)d_in[1],
                                                      (__nv_bfloat16*)d_out, maps);
}
```
